```python
import torch

def _softmax(x, axis=-1):
    return torch.softmax(x, dim=axis)
def _gelu(x):
    return torch.nn.functional.gelu(x, approximate="tanh")
def _silu(x):
    return torch.nn.functional.silu(x)
def _sigmoid(x):
    return torch.sigmoid(x)
def _layernorm(x, axis=-1, eps=1e-5):
    m = x.mean(dim=axis, keepdim=True)
    v = x.var(dim=axis, keepdim=True, unbiased=False)
    return (x - m) / torch.sqrt(v + eps)
def _scatter_add(tgt, idx, src, axis=0):
    return tgt.clone().index_add_(axis, idx, src)
def _segment_sum(src, seg, n):
    out = torch.zeros((n,) + src.shape[1:], dtype=src.dtype)
    return out.index_add_(0, seg, src)
def _pad(x, pw):
    flat = tuple(v for pair in reversed(pw) for v in pair)
    return torch.nn.functional.pad(x, flat)

kernel_name = 'recurrent_scan__ssm_conv_s4d__mixer_channel_mlp__prompt'

def setup_inputs():

    _w = (lambda a: (lambda t: t.to(torch.bfloat16) if t.is_floating_point() else t)(torch.as_tensor(a)))
    def _A_setup():
        Bsz, L, D, N = 1, 2048, 448, 256
        return {
            "u": _w((lambda *s: torch.randn(*s, dtype=torch.bfloat16) * 0.05)(Bsz, L, D)),
            "log_A_real": _w((lambda *s: torch.randn(*s, dtype=torch.bfloat16) * 3.2)(D, N) * 0.5),
            "A_imag": _w((lambda *s: torch.randn(*s, dtype=torch.bfloat16) * 0.2)(D, N) * 3.14),
            "C_real": _w((lambda *s: torch.randn(*s, dtype=torch.bfloat16) * 0.8)(D, N) / N ** 0.5),
            "C_imag": _w((lambda *s: torch.randn(*s, dtype=torch.bfloat16) * 0.8)(D, N) / N ** 0.5),
            "log_dt": _w((lambda *s: torch.randn(*s, dtype=torch.bfloat16) * 0.2)(D) * 0.5 - 4.0),
            "D_skip": _w((lambda *s: torch.randn(*s, dtype=torch.bfloat16) * 0.2)(D)),
        }
    _A_in = _A_setup()

    def _B_setup():
        B, S, D, F = 1, 2048, 448, 1792
        return {
            "x": _w((lambda *s: torch.randn(*s, dtype=torch.bfloat16) * 0.05)(B, S, D)),
            "w1": _w((lambda *s: torch.randn(*s, dtype=torch.bfloat16) * 1.6)(D, F) * (D ** -0.5)),
            "b1": _w((lambda *s: torch.randn(*s, dtype=torch.bfloat16) * 0.8)(F)),
            "w2": _w((lambda *s: torch.randn(*s, dtype=torch.bfloat16) * 0.1)(F, D) * (F ** -0.5)),
            "b2": _w((lambda *s: torch.randn(*s, dtype=torch.bfloat16) * 0.1)(D)),
        }
    _B_in = _B_setup()

    return {
        "A_u": _A_in["u"],
        "A_log_A_real": _A_in["log_A_real"],
        "A_A_imag": _A_in["A_imag"],
        "A_C_real": _A_in["C_real"],
        "A_C_imag": _A_in["C_imag"],
        "A_log_dt": _A_in["log_dt"],
        "A_D_skip": _A_in["D_skip"],
        "B_x": _B_in["x"],
        "B_w1": _B_in["w1"],
        "B_b1": _B_in["b1"],
        "B_w2": _B_in["w2"],
        "B_b2": _B_in["b2"],
    }

def reference(A_u, A_log_A_real, A_A_imag, A_C_real, A_C_imag, A_log_dt, A_D_skip, B_x, B_w1, B_b1, B_w2, B_b2):
    def _A_ref(u, log_A_real, A_imag, C_real, C_imag, log_dt, D_skip):
        L = u.shape[1]
        dt = torch.exp(log_dt)
        A = -torch.exp(log_A_real) + 1j * A_imag
        C = (C_real + 1j * C_imag) * dt[:, None]
        pos = (lambda x, dt: x.to(dt))(torch.arange(L), log_dt.dtype)
        P = torch.exp((A * dt[:, None])[:, :, None] * pos[None, None, :])
        K = 2.0 * torch.einsum("dn,dnl->dl", C, P).real
        L2 = 2 * L
        u_t = (lambda x, *d: x.permute(*d))(u, 0, 2, 1)
        Kf = (lambda x, *a, **k: torch.fft.rfft(x.float(), *a, **k))(K, L2)
        Uf = (lambda x, *a, **k: torch.fft.rfft(x.float(), *a, **k))(u_t, L2)
        y = (lambda x, *a, **k: torch.fft.irfft(x, *a, **k).to(torch.bfloat16))(Uf * Kf[None, :, :], L2)[:, :, :L]
        y = (lambda x, *d: x.permute(*d))(y, 0, 2, 1)
        return y + u * D_skip[None, None, :]

    def _B_ref(x, w1, b1, w2, b2):
        y = _layernorm(x, axis=-1)
        h = _gelu(torch.einsum("bsd,df->bsf", y, w1) + b1)
        return torch.einsum("bsf,fd->bsd", h, w2) + b2

    x = A_u
    xn = _layernorm(x, axis=-1)
    s = _A_ref(xn, A_log_A_real, A_A_imag, A_C_real, A_C_imag, A_log_dt, A_D_skip)
    g = _silu(_B_ref(xn, B_w1, B_b1, B_w2, B_b2))
    return x + s * g
```

```cpp
#include <cuda_runtime.h>
#include <cuda.h>
#include <cuda_bf16.h>
#include <cuda_fp16.h>
#include <stdint.h>

namespace {

constexpr int LSEQ = 2048, DM = 448, NMODE = 256, FF = 1792;
constexpr int NMLP = 112, NHELP = 20, NCTA = NMLP + NHELP;
constexpr int CH_EXP = 2 * NMLP + 6 * NHELP;
constexpr int FT0 = 6, DEPSZ = 1296;
#define HELP_HOLD 0
constexpr int PP_K = 5, CHAIN_IT = 2;
constexpr int NS = 9, SLOT = 16384, NFILL = 36;
constexpr int T_XP = 0;
constexpr int T_U2O = 4608, U2SZ = 3360;
constexpr int T_U3O = T_U2O + 2 * U2SZ, U3SZ = 2048;
constexpr int T_STG = T_U3O + 3 * U3SZ;
constexpr int STG_W = 7168;
constexpr int T_TAB = T_STG + 2 * STG_W;
constexpr int TD0 = 0, TD1 = 1216;
constexpr int TT2 = 2368, TT2SZ = 192;
constexpr int TT3 = TT2 + 2 * TT2SZ, TT3SZ = 384;
constexpr int TABSZ = TT3 + 2 * TT3SZ;
constexpr int TEAM = T_TAB + TABSZ + 64 - 128 + 128;
constexpr int O_AUX = NS * SLOT;
constexpr int O_SUM = O_AUX + 17408;
constexpr int O_BEXT = O_AUX + 2 * TEAM;
constexpr int O_STATS = O_BEXT + 4096;
constexpr int O_DEP = O_BEXT;
constexpr int O_CSS = O_DEP + 8 * DEPSZ;
constexpr int O_FILL = O_CSS + 1024;
constexpr int O_BAR = O_FILL + 1024;
constexpr int O_REL = O_BAR + 128;
constexpr int SMEM_USED = O_REL + 64;
constexpr int SMEM_BYTES = SMEM_USED + 1024;
static_assert(SMEM_BYTES <= 232448, "smem");
static_assert(6 * TEAM + 16 * 912 <= SMEM_USED, "helper smem");
static_assert(TEAM % 16 == 0 && O_BEXT % 128 == 0 && O_CSS % 16 == 0, "align");

enum { BAR_PP = 5, BAR_AUX = 7, BAR_A = 8, BAR_B = 9, BAR_C = 10, BAR_INIT = 11, BAR_D = 12, BAR_K = 13, BAR_LN = 14, BAR_A2 = 15 };

struct Scratch {
    unsigned cnt[NCTA * 8];
    unsigned hint[12 * 32];
    unsigned cs[FF * 4];
    uint4 stats[LSEQ];
    uint4 kexp[NMLP * 128];
    unsigned pflag[16 * 7 * 64];
    __half xnT[DM * LSEQ];
    __nv_bfloat16 sT[DM * LSEQ];
    uint4 part[16 * 7 * 7 * 1024];
};
__device__ Scratch g_scr;
#define TL(k)
#define TLV(k, v)

struct Params {
    const __nv_bfloat16 *x, *lar, *aim, *cre, *cim, *ldt, *dsk, *w1, *b1, *b2;
    __nv_bfloat16* out;
    Scratch* S;
};

__device__ __forceinline__ uint32_t smem_u32(const void* p) { return (uint32_t)__cvta_generic_to_shared(p); }
__device__ __forceinline__ void mbar_init(uint32_t bar, uint32_t cnt) { asm volatile("mbarrier.init.shared::cta.b64 [%0], %1;" :: "r"(bar), "r"(cnt)); }
__device__ __forceinline__ void mbar_expect_tx(uint32_t bar, uint32_t bytes) { asm volatile("mbarrier.arrive.expect_tx.shared::cta.b64 _, [%0], %1;" :: "r"(bar), "r"(bytes) : "memory"); }
__device__ __forceinline__ void mbar_wait(uint32_t bar, uint32_t parity) {
    #pragma unroll 1
    for (int i = 0; i < (1 << 16); i++) {
        uint32_t ok;
        asm volatile("{\n.reg .pred p;\nmbarrier.try_wait.parity.shared::cta.b64 p, [%1], %2;\nselp.u32 %0, 1, 0, p;\n}" : "=r"(ok) : "r"(bar), "r"(parity) : "memory");
        if (ok) return;
    }
}
__device__ __forceinline__ void bar_sync(int id, int n) { asm volatile("bar.sync %0, %1;" :: "r"(id), "r"(n) : "memory"); }
__device__ __forceinline__ void bar_arrive(int id, int n) { asm volatile("bar.arrive %0, %1;" :: "r"(id), "r"(n) : "memory"); }
__device__ __forceinline__ unsigned ld_acquire(const unsigned* p) { unsigned v; asm volatile("ld.acquire.gpu.global.u32 %0, [%1];" : "=r"(v) : "l"(p) : "memory"); return v; }
__device__ __forceinline__ unsigned ld_relaxed(const unsigned* p) { unsigned v; asm volatile("ld.relaxed.gpu.global.u32 %0, [%1];" : "=r"(v) : "l"(p) : "memory"); return v; }
__device__ __forceinline__ void red_release(unsigned* p, unsigned v) { asm volatile("red.release.gpu.global.add.u32 [%0], %1;" :: "l"(p), "r"(v) : "memory"); }
__device__ __forceinline__ void red_relaxed(unsigned* p) { asm volatile("red.relaxed.gpu.global.add.u32 [%0], 1;" :: "l"(p) : "memory"); }
__device__ __forceinline__ void wait_hint(const unsigned* p, unsigned target) {
    if ((threadIdx.x & 31) == 0) {
        #pragma unroll 1
        for (int i = 0; i < (1 << 16); i++) { if ((int)(ld_relaxed(p) - target) >= 0) break; __nanosleep(150); }
    }
    __syncwarp();
}
__device__ __forceinline__ uint4 ld_relaxed_v4(const void* p) {
    uint4 v;
    asm volatile("{\n.reg .b128 t;\nld.relaxed.gpu.global.b128 t, [%4];\nmov.b128 {%0,%1,%2,%3}, t;\n}" : "=r"(v.x), "=r"(v.y), "=r"(v.z), "=r"(v.w) : "l"(p) : "memory");
    return v;
}
__device__ __forceinline__ void st_relaxed_v4(void* p, uint4 v) {
    asm volatile("{\n.reg .b128 t;\nmov.b128 t, {%1,%2,%3,%4};\nst.relaxed.gpu.global.b128 [%0], t;\n}" :: "l"(p), "r"(v.x), "r"(v.y), "r"(v.z), "r"(v.w) : "memory");
}
__device__ __forceinline__ void st_relaxed_v2(void* p, uint32_t x, uint32_t y) {
    asm volatile("{\n.reg .b64 t;\nmov.b64 t, {%1,%2};\nst.relaxed.gpu.global.b64 [%0], t;\n}" :: "l"(p), "r"(x), "r"(y) : "memory");
}
__device__ __forceinline__ uint4 ld_relaxed_2x64(const void* p) {
    uint4 v;
    asm volatile("{\n.reg .b64 a, b;\nld.relaxed.gpu.global.v2.b64 {a, b}, [%4];\nmov.b64 {%0,%1}, a;\nmov.b64 {%2,%3}, b;\n}" : "=r"(v.x), "=r"(v.y), "=r"(v.z), "=r"(v.w) : "l"(p) : "memory");
    return v;
}
__device__ __forceinline__ uint4 ld_relaxed_4x32(const void* p) {
    uint4 v; asm volatile("ld.relaxed.gpu.global.v4.u32 {%0,%1,%2,%3}, [%4];" : "=r"(v.x), "=r"(v.y), "=r"(v.z), "=r"(v.w) : "l"(p) : "memory"); return v;
}
__device__ __forceinline__ uint4 ld_cg_v4(const void* p) {
    uint4 v; asm volatile("ld.global.cg.v4.u32 {%0,%1,%2,%3}, [%4];" : "=r"(v.x), "=r"(v.y), "=r"(v.z), "=r"(v.w) : "l"(p) : "memory"); return v;
}
__device__ __forceinline__ uint4 lds128(uint32_t a) { uint4 v; asm volatile("ld.shared.v4.u32 {%0,%1,%2,%3}, [%4];" : "=r"(v.x), "=r"(v.y), "=r"(v.z), "=r"(v.w) : "r"(a) : "memory"); return v; }
__device__ __forceinline__ uint32_t lds32(uint32_t a) { uint32_t v; asm volatile("ld.shared.u32 %0, [%1];" : "=r"(v) : "r"(a) : "memory"); return v; }
__device__ __forceinline__ float ldsf(uint32_t a) { return __uint_as_float(lds32(a)); }
__device__ __forceinline__ void sts128(uint32_t a, uint32_t x, uint32_t y, uint32_t z, uint32_t w) { asm volatile("st.shared.v4.u32 [%0], {%1,%2,%3,%4};" :: "r"(a), "r"(x), "r"(y), "r"(z), "r"(w) : "memory"); }
__device__ __forceinline__ void sts32(uint32_t a, uint32_t x) { asm volatile("st.shared.u32 [%0], %1;" :: "r"(a), "r"(x) : "memory"); }
__device__ __forceinline__ void ldsm4(uint32_t a, uint32_t& r0, uint32_t& r1, uint32_t& r2, uint32_t& r3) {
    asm volatile("ldmatrix.sync.aligned.m8n8.x4.shared.b16 {%0,%1,%2,%3}, [%4];" : "=r"(r0), "=r"(r1), "=r"(r2), "=r"(r3) : "r"(a) : "memory");
}
__device__ __forceinline__ void ldsm4t(uint32_t a, uint32_t& r0, uint32_t& r1, uint32_t& r2, uint32_t& r3) {
    asm volatile("ldmatrix.sync.aligned.m8n8.x4.trans.shared.b16 {%0,%1,%2,%3}, [%4];" : "=r"(r0), "=r"(r1), "=r"(r2), "=r"(r3) : "r"(a) : "memory");
}
__device__ __forceinline__ void ldsm2t(uint32_t a, uint32_t& r0, uint32_t& r1) {
    asm volatile("ldmatrix.sync.aligned.m8n8.x2.trans.shared.b16 {%0,%1}, [%2];" : "=r"(r0), "=r"(r1) : "r"(a) : "memory");
}
__device__ __forceinline__ void stsm4(uint32_t a, uint32_t r0, uint32_t r1, uint32_t r2, uint32_t r3) {
    asm volatile("stmatrix.sync.aligned.m8n8.x4.shared.b16 [%0], {%1,%2,%3,%4};" :: "r"(a), "r"(r0), "r"(r1), "r"(r2), "r"(r3) : "memory");
}
__device__ __forceinline__ void stsm4t(uint32_t a, uint32_t r0, uint32_t r1, uint32_t r2, uint32_t r3) {
    asm volatile("stmatrix.sync.aligned.m8n8.x4.trans.shared.b16 [%0], {%1,%2,%3,%4};" :: "r"(a), "r"(r0), "r"(r1), "r"(r2), "r"(r3) : "memory");
}
__device__ __forceinline__ void mma_f16(float (&c)[4], uint32_t a0, uint32_t a1, uint32_t a2, uint32_t a3, uint32_t b0, uint32_t b1) {
    asm volatile("mma.sync.aligned.m16n8k16.row.col.f32.f16.f16.f32 {%0,%1,%2,%3}, {%4,%5,%6,%7}, {%8,%9}, {%0,%1,%2,%3};"
        : "+f"(c[0]), "+f"(c[1]), "+f"(c[2]), "+f"(c[3]) : "r"(a0), "r"(a1), "r"(a2), "r"(a3), "r"(b0), "r"(b1));
}
__device__ __forceinline__ uint32_t pack_bf16(float lo, float hi) { uint32_t r; asm("cvt.rn.bf16x2.f32 %0, %1, %2;" : "=r"(r) : "f"(hi), "f"(lo)); return r; }
__device__ __forceinline__ uint32_t pack_f16(float lo, float hi) { uint32_t r; asm("cvt.rn.f16x2.f32 %0, %1, %2;" : "=r"(r) : "f"(hi), "f"(lo)); return r; }
__device__ __forceinline__ float bf_lo(uint32_t v) { return __uint_as_float(v << 16); }
__device__ __forceinline__ float bf_hi(uint32_t v) { return __uint_as_float(v & 0xffff0000u); }
__device__ __forceinline__ float rbf(float v) { return __uint_as_float(pack_bf16(0.f, v)); }
__device__ __forceinline__ float tanh_fast(float v) { float r; asm("tanh.approx.f32 %0, %1;" : "=f"(r) : "f"(v)); return r; }
__device__ __forceinline__ float ex2_fast(float v) { float r; asm("ex2.approx.ftz.f32 %0, %1;" : "=f"(r) : "f"(v)); return r; }
__device__ __forceinline__ __half2 H2(uint32_t v) { return *reinterpret_cast<__half2*>(&v); }
__device__ __forceinline__ uint32_t U32(__half2 v) { return *reinterpret_cast<uint32_t*>(&v); }
__device__ __forceinline__ __nv_bfloat162 B2(uint32_t v) { return *reinterpret_cast<__nv_bfloat162*>(&v); }
__device__ __forceinline__ uint32_t U32(__nv_bfloat162 v) { return *reinterpret_cast<uint32_t*>(&v); }
__device__ __forceinline__ uint32_t hadd2u(uint32_t a, uint32_t b) { return U32(__hadd2(H2(a), H2(b))); }
__device__ __forceinline__ float warp_sum(float v) {
    #pragma unroll
    for (int o = 16; o > 0; o >>= 1) v += __shfl_xor_sync(0xffffffffu, v, o);
    return v;
}

__device__ __forceinline__ uint64_t make_desc(uint32_t addr, uint32_t lbo, uint32_t sbo) {
    return (uint64_t)((addr & 0x3FFFF) >> 4) | ((uint64_t)(lbo >> 4) << 16) | ((uint64_t)(sbo >> 4) << 32) | ((uint64_t)1 << 62);
}
#define ACC8(d, b) "+f"(d[b+0]), "+f"(d[b+1]), "+f"(d[b+2]), "+f"(d[b+3]), "+f"(d[b+4]), "+f"(d[b+5]), "+f"(d[b+6]), "+f"(d[b+7])
__device__ __forceinline__ void wgmma_n256(float (&d)[128], uint64_t da, uint64_t db, int scale_d) {
    asm volatile("{\n.reg .pred p;\nsetp.ne.b32 p, %130, 0;\n"
        "wgmma.mma_async.sync.aligned.m64n256k16.f32.bf16.bf16 {"
        "%0,%1,%2,%3,%4,%5,%6,%7,%8,%9,%10,%11,%12,%13,%14,%15,%16,%17,%18,%19,%20,%21,%22,%23,%24,%25,%26,%27,%28,%29,%30,%31,"
        "%32,%33,%34,%35,%36,%37,%38,%39,%40,%41,%42,%43,%44,%45,%46,%47,%48,%49,%50,%51,%52,%53,%54,%55,%56,%57,%58,%59,%60,%61,%62,%63,"
        "%64,%65,%66,%67,%68,%69,%70,%71,%72,%73,%74,%75,%76,%77,%78,%79,%80,%81,%82,%83,%84,%85,%86,%87,%88,%89,%90,%91,%92,%93,%94,%95,"
        "%96,%97,%98,%99,%100,%101,%102,%103,%104,%105,%106,%107,%108,%109,%110,%111,%112,%113,%114,%115,%116,%117,%118,%119,%120,%121,%122,%123,%124,%125,%126,%127"
        "}, %128, %129, p, 1, 1, 0, 1;\n}\n"
        : ACC8(d, 0), ACC8(d, 8), ACC8(d, 16), ACC8(d, 24), ACC8(d, 32), ACC8(d, 40), ACC8(d, 48), ACC8(d, 56),
          ACC8(d, 64), ACC8(d, 72), ACC8(d, 80), ACC8(d, 88), ACC8(d, 96), ACC8(d, 104), ACC8(d, 112), ACC8(d, 120)
        : "l"(da), "l"(db), "r"(scale_d));
}
template <int scale_d>
__device__ __forceinline__ void wgmma_n64_rs(float (&d)[32], uint32_t a0, uint32_t a1, uint32_t a2, uint32_t a3, uint32_t db) {
    asm volatile("{\n.reg .pred p;\n.reg .b64 db;\nsetp.ne.b32 p, %37, 0;\nmov.b64 db, {%36, 0x40000040};\n"
        "wgmma.mma_async.sync.aligned.m64n64k16.f32.bf16.bf16 {"
        "%0,%1,%2,%3,%4,%5,%6,%7,%8,%9,%10,%11,%12,%13,%14,%15,%16,%17,%18,%19,%20,%21,%22,%23,%24,%25,%26,%27,%28,%29,%30,%31"
        "}, {%32,%33,%34,%35}, db, p, 1, 1, 1;\n}\n"
        : ACC8(d, 0), ACC8(d, 8), ACC8(d, 16), ACC8(d, 24)
        : "r"(a0), "r"(a1), "r"(a2), "r"(a3), "r"(db), "n"(scale_d));
}
#define WG_FENCE() asm volatile("wgmma.fence.sync.aligned;" ::: "memory")
#define WG_COMMIT() asm volatile("wgmma.commit_group.sync.aligned;" ::: "memory")
#define WG_WAIT(n) asm volatile("wgmma.wait_group.sync.aligned " #n ";" ::: "memory")
template <int N> __device__ __forceinline__ void reg_fence(float (&d)[N]) {
    #pragma unroll
    for (int i = 0; i < N; i++) asm volatile("" : "+f"(d[i]) :: "memory");
}

__device__ __forceinline__ void wgmma_n256_rs(float (&d)[128], uint32_t a0, uint32_t a1, uint64_t db) {
    asm volatile("{\n.reg .pred p;\nsetp.ne.b32 p, 1, 0;\n"
        "wgmma.mma_async.sync.aligned.m64n256k16.f32.bf16.bf16 {"
        "%0,%1,%2,%3,%4,%5,%6,%7,%8,%9,%10,%11,%12,%13,%14,%15,%16,%17,%18,%19,%20,%21,%22,%23,%24,%25,%26,%27,%28,%29,%30,%31,"
        "%32,%33,%34,%35,%36,%37,%38,%39,%40,%41,%42,%43,%44,%45,%46,%47,%48,%49,%50,%51,%52,%53,%54,%55,%56,%57,%58,%59,%60,%61,%62,%63,"
        "%64,%65,%66,%67,%68,%69,%70,%71,%72,%73,%74,%75,%76,%77,%78,%79,%80,%81,%82,%83,%84,%85,%86,%87,%88,%89,%90,%91,%92,%93,%94,%95,"
        "%96,%97,%98,%99,%100,%101,%102,%103,%104,%105,%106,%107,%108,%109,%110,%111,%112,%113,%114,%115,%116,%117,%118,%119,%120,%121,%122,%123,%124,%125,%126,%127"
        "}, {%128, %129, %130, %130}, %131, p, 1, 1, 0;\n}\n"
        : ACC8(d, 0), ACC8(d, 8), ACC8(d, 16), ACC8(d, 24), ACC8(d, 32), ACC8(d, 40), ACC8(d, 48), ACC8(d, 56),
          ACC8(d, 64), ACC8(d, 72), ACC8(d, 80), ACC8(d, 88), ACC8(d, 96), ACC8(d, 104), ACC8(d, 112), ACC8(d, 120)
        : "r"(a0), "r"(a1), "r"(0u), "l"(db));
}
__device__ __forceinline__ void tma_fill(const CUtensorMap* maps, uint32_t dst, uint32_t bar, uint32_t moff, uint32_t c0, uint32_t c1, uint32_t c2) {
    mbar_expect_tx(bar, SLOT);
    asm volatile("cp.async.bulk.tensor.3d.shared::cluster.global.mbarrier::complete_tx::bytes [%0], [%1, {%3, %4, %5}], [%2];"
        :: "r"(dst), "l"(reinterpret_cast<const char*>(maps) + moff), "r"(bar), "r"(c0), "r"(c1), "r"(c2) : "memory");
}
__device__ __forceinline__ void ldg_v2(const void* p, uint32_t& x, uint32_t& y) { asm volatile("ld.global.nc.v2.u32 {%0,%1}, [%2];" : "=r"(x), "=r"(y) : "l"(p)); }
__device__ __forceinline__ bool elect_one() {
    uint32_t r; asm volatile("{\n.reg .pred p;\nelect.sync _|p, 0xffffffff;\nselp.u32 %0, 1, 0, p;\n}" : "=r"(r)); return r;
}
__device__ __forceinline__ void sts16(uint32_t a, uint32_t x) { asm volatile("st.shared.u16 [%0], %1;" :: "r"(a), "h"((uint16_t)x) : "memory"); }
__device__ __forceinline__ float rcp_fast(float v) { float r; asm("rcp.approx.ftz.f32 %0, %1;" : "=f"(r) : "f"(v)); return r; }
__device__ __forceinline__ float sqrt_fast(float v) { float r; asm("sqrt.approx.ftz.f32 %0, %1;" : "=f"(r) : "f"(v)); return r; }
__device__ __forceinline__ float half_sum(float v) {
    #pragma unroll
    for (int o = 8; o > 0; o >>= 1) v += __shfl_xor_sync(0xffffffffu, v, o);
    return v;
}

struct Cx { float r, i; };
__device__ __forceinline__ Cx cmul(Cx a, Cx b) { return {fmaf(a.r, b.r, -a.i * b.i), fmaf(a.r, b.i, a.i * b.r)}; }
__device__ __forceinline__ Cx csqr(Cx a) { return {fmaf(a.r, a.r, -a.i * a.i), (a.r + a.r) * a.i}; }
__device__ __forceinline__ Cx anchor(float lm, float th, float tl, float p) {
    float mag = ex2_fast(lm * p);
    float u = th * p;
    float f = fmaf(tl, p, u - rintf(u)) * 6.283185307179586f;
    return {mag * __cosf(f), mag * __sinf(f)};
}
__device__ __forceinline__ void hcmul(uint32_t pr, uint32_t pi, uint32_t y, uint32_t& orr, uint32_t& oi) {
    __half2 yr = __low2half2(H2(y)), yi = __high2half2(H2(y));
    orr = U32(__hfma2(H2(pr), yr, __hneg2(__hmul2(H2(pi), yi))));
    oi = U32(__hfma2(H2(pr), yi, __hmul2(H2(pi), yr)));
}

struct Maps { CUtensorMap m[3]; };

struct KPar {
    uint2 lar, aim, cre, cim, cre2, cim2; uint32_t ldt, dskr;
    __device__ __forceinline__ void load(const Params& P, int ch, int off) {
        const int po = ch * NMODE + off;
        ldg_v2(P.lar + po, lar.x, lar.y); ldg_v2(P.aim + po, aim.x, aim.y);
        ldg_v2(P.cre + po, cre.x, cre.y); ldg_v2(P.cim + po, cim.x, cim.y);
        asm volatile("ld.global.nc.u16 %0, [%1];" : "=r"(ldt) : "l"(P.ldt + ch));
        ldg_v2(P.cre + (po ^ 4), cre2.x, cre2.y); ldg_v2(P.cim + (po ^ 4), cim2.x, cim2.y);
        asm volatile("ld.global.nc.u16 %0, [%1];" : "=r"(dskr) : "l"(P.dsk + ch));
    }
};
struct KGen : KPar {
    float dt, cscale, yscale, dtap, acc[5][4], k2048;
    uint32_t zero;
    __device__ __forceinline__ void consts() {
        const float l = __uint_as_float(ldt << 16), t = l * 1.4426950408889634f;
        dt = rbf(ex2_fast(t) * fmaf(fmaf(l, 1.4426950408889634f, -t) + l * 1.925963033500e-8f, 0.6931471805599453f, 1.f));
        uint32_t mx = __vimax3_u16x2(__vimax3_u16x2(cre.x & 0x7fff7fffu, cre.y & 0x7fff7fffu, cim.x & 0x7fff7fffu),
                                     __vimax3_u16x2(cim.y & 0x7fff7fffu, cre2.x & 0x7fff7fffu, cre2.y & 0x7fff7fffu),
                                     __vmaxu2(cim2.x & 0x7fff7fffu, cim2.y & 0x7fff7fffu));
        mx = __reduce_max_sync(0xffffffffu, max(mx & 0xffffu, mx >> 16));
        zero = mx >> 16;
        const int ec = (int)(__float_as_uint(__uint_as_float(mx << 16) * 2.f * dt) >> 23) + 1, ed = (int)((dskr & 0x7fffu) >> 7) - 13;
        const uint32_t eb = min(max(max(ec, ed), 2), 253);
        const float inv = __uint_as_float((254 - eb) << 23);
        yscale = __uint_as_float(eb << 23);
        cscale = 2.f * dt * inv;
        dtap = __uint_as_float(dskr << 16) * inv;
        k2048 = 0.f;
        #pragma unroll
        for (int t5 = 0; t5 < 5; t5++) { acc[t5][0] = acc[t5][1] = acc[t5][2] = acc[t5][3] = 0.f; }
    }
    __device__ __forceinline__ void pass(uint32_t stg, int lane) {
        const float lar = bf_lo(this->lar.x), aim = bf_lo(this->aim.x);
        const Cx X0 = {bf_lo(cre.x) * cscale, bf_lo(cim.x) * cscale};
        this->lar.x = __funnelshift_r(this->lar.x, this->lar.y, 16); this->lar.y >>= 16; this->aim.x = __funnelshift_r(this->aim.x, this->aim.y, 16); this->aim.y >>= 16;
        cre.x = __funnelshift_r(cre.x, cre.y, 16); cre.y >>= 16; cim.x = __funnelshift_r(cim.x, cim.y, 16); cim.y >>= 16;
        const float lm = -rbf(ex2_fast(lar * 1.4426950408889634f)) * dt * 1.4426950408889634f;
        const float zi = aim * dt;
        const float th = zi * 0.15915494309189535f;
        const float tl = fmaf(zi, 0.15915494309189535f, -th) + zi * 6.4206382e-09f;
        const Cx E1 = anchor(lm, th, tl, 1.f), Y1 = anchor(lm, th, tl, 32.f);
        const Cx E2 = csqr(E1), E3 = cmul(E2, E1), E4 = csqr(E2), E5 = cmul(E4, E1), E6 = csqr(E3), E7 = cmul(E4, E3), E8 = csqr(E4);
        const Cx X1 = cmul(X0, E8), X2 = cmul(X1, E8), X3 = cmul(X2, E8);
        const Cx Y2 = csqr(Y1), Y3 = cmul(Y2, Y1), G1 = csqr(Y2), G2 = csqr(G1), G3 = cmul(G2, G1), G4 = csqr(G2), G5 = cmul(G4, G1), G6 = csqr(G3), G7 = cmul(G4, G3), G8 = csqr(G4);
        { const Cx Z = csqr(G8); k2048 += fmaf(X0.r, Z.r, -X0.i * Z.i); }
        const uint32_t sa = stg + lane * 16;
        __syncwarp();
        {
            const uint32_t xr01 = pack_f16(X0.r, X1.r), xr23 = pack_f16(X2.r, X3.r), xn01 = pack_f16(-X0.i, -X1.i), xn23 = pack_f16(-X2.i, -X3.i);
            uint32_t a, bq, c, d, e, f, gq, hq;
            const uint32_t y1 = pack_f16(Y1.r, -Y1.i), y2 = pack_f16(Y2.r, -Y2.i), y3 = pack_f16(Y3.r, -Y3.i);
            hcmul(xr01, xn01, y1, a, bq); hcmul(xr23, xn23, y1, c, d);
            sts128(sa + 0 * 512, xr01, xr23, a, c); sts128(sa + 2 * 512, xn01, xn23, bq, d);
            hcmul(xr01, xn01, y2, a, bq); hcmul(xr23, xn23, y2, c, d); hcmul(xr01, xn01, y3, e, f); hcmul(xr23, xn23, y3, gq, hq);
            sts128(sa + 1 * 512, a, c, e, gq); sts128(sa + 3 * 512, bq, d, f, hq);
        }
        {
            const uint32_t r02 = pack_f16(1.f, E2.r), r46 = pack_f16(E4.r, E6.r), r13 = pack_f16(E1.r, E3.r), r57 = pack_f16(E5.r, E7.r);
            const uint32_t i02 = pack_f16(0.f, E2.i), i46 = pack_f16(E4.i, E6.i), i13 = pack_f16(E1.i, E3.i), i57 = pack_f16(E5.i, E7.i);
            uint32_t a, bq, c, d, e, f, gq, hq;
            sts128(sa + 4 * 512, r02, r46, r13, r57); sts128(sa + 5 * 512, i02, i46, i13, i57);
            const uint32_t g1 = pack_f16(G1.r, G1.i), g2 = pack_f16(G2.r, G2.i), g3 = pack_f16(G3.r, G3.i);
            hcmul(r02, i02, g1, a, bq); hcmul(r46, i46, g1, c, d); hcmul(r13, i13, g1, e, f); hcmul(r57, i57, g1, gq, hq);
            sts128(sa + 6 * 512, a, c, e, gq); sts128(sa + 7 * 512, bq, d, f, hq);
            hcmul(r02, i02, g2, a, bq); hcmul(r46, i46, g2, c, d); hcmul(r02, i02, g3, e, f); hcmul(r46, i46, g3, gq, hq);
            sts128(sa + 8 * 512, a, c, e, gq); sts128(sa + 9 * 512, bq, d, f, hq);
            const uint32_t r45 = pack_f16(G4.r, G5.r), r67 = pack_f16(G6.r, G7.r), i45 = pack_f16(G4.i, G5.i), i67 = pack_f16(G6.i, G7.i);
            const uint32_t e4 = __byte_perm(r46, i46, 0x5410), g4 = __byte_perm(r45, i45, 0x5410), g8 = pack_f16(G8.r, G8.i);
            hcmul(r45, i45, e4, a, bq); hcmul(r67, i67, e4, c, d);
            sts128(sa + 10 * 512, r45, r67, a, c); sts128(sa + 11 * 512, i45, i67, bq, d);
            hcmul(r45, i45, g4, a, bq); hcmul(r67, i67, g4, c, d); hcmul(r45, i45, g8, e, f); hcmul(r67, i67, g8, gq, hq);
            sts128(sa + 12 * 512, a, c, e, gq); sts128(sa + 13 * 512, bq, d, f, hq);
        }
        __syncwarp();
    }
    __device__ __forceinline__ void contract(uint32_t stg, int lane) {
        float (&kacc)[5][4] = acc;
        #pragma unroll
        for (int ks = 0; ks < 4; ks++) {
            const uint32_t la = stg + (lane >> 3) * 512 + (ks * 8 + (lane & 7)) * 16;
            uint32_t a0, a1, a2, a3, b0, b1, b2, b3, c0, c1, c2, c3, d0, d1;
            ldsm4t(la, a0, a1, a2, a3);
            ldsm4t(la + 4 * 512, b0, b1, b2, b3);
            ldsm4t(la + 8 * 512, c0, c1, c2, c3);
            ldsm2t(la + 12 * 512, d0, d1);
            mma_f16(kacc[0], a0, a1, a2, a3, b0, b1); mma_f16(kacc[1], a0, a1, a2, a3, b2, b3);
            mma_f16(kacc[2], a0, a1, a2, a3, c0, c1); mma_f16(kacc[3], a0, a1, a2, a3, c2, c3);
            mma_f16(kacc[4], a0, a1, a2, a3, d0, d1);
        }
    }
    __device__ __forceinline__ void deposit(uint32_t dep, int lane, bool lead) {
        if (lead) acc[0][0] += dtap;
        const float k512 = __shfl_sync(0xffffffffu, acc[3][0], 0);
        if (lane == 31) acc[2][3] -= k512;
        k2048 = warp_sum(k2048);
        __syncwarp();
        #pragma unroll
        for (int t = 0; t < 5; t++) {
            sts32(dep + t * 256 + lane * 4, pack_f16(acc[t][0], acc[t][1]));
            sts32(dep + t * 256 + 128 + lane * 4, pack_f16(acc[t][2], acc[t][3]));
        }
        sts128(dep + 1280, __float_as_uint(k2048), __float_as_uint(yscale), 0, 0);
    }
};

struct Taps { uint32_t kv[5]; float k2, yscale; };
template <int ND>
__device__ __forceinline__ Taps sum_deposits(uint32_t d0, uint32_t s1, uint32_t s2, int tt) {
    Taps T; float ks[10]; T.k2 = 0.f;
    #pragma unroll
    for (int t = 0; t < 10; t++) ks[t] = 0.f;
    #pragma unroll
    for (int i = 0; i < ND; i++) {
        const uint32_t og = d0 + (i & 1) * s1 + (i >> 1) * s2;
        #pragma unroll
        for (int t = 0; t < 5; t++) { const float2 v = __half22float2(H2(lds32(og + t * 256 + tt * 4))); ks[2 * t] += v.x; ks[2 * t + 1] += v.y; }
        T.k2 += ldsf(og + 1280);
    }
    T.yscale = ldsf(d0 + 1284);
    #pragma unroll
    for (int t = 0; t < 5; t++) T.kv[t] = pack_f16(ks[2 * t], ks[2 * t + 1]);
    return T;
}
__device__ __forceinline__ void scatter_taps(Taps& T, uint32_t tb, int tt) {
    const int lane = tt & 31, w = tt >> 5, g = lane >> 2, q = lane & 3;
    uint32_t (&kv)[5] = T.kv;
    const int jj = g + 8 * w;
    const uint32_t tab = tb + T_TAB;
    const uint32_t d01 = tab + TD0 + 2 * (544 - (8 * jj + (q & 1) * 4 + (q >> 1)));
    #pragma unroll
    for (int t = 0; t < 2; t++) {
        sts16(d01 - t * 256, kv[t]); sts16(d01 - t * 256 + (TD1 + 2), kv[t]);
        sts16(d01 - t * 256 - 4, kv[t] >> 16); sts16(d01 - t * 256 - 4 + (TD1 + 2), kv[t] >> 16);
    }
    const int p2 = 256 + 128 * (q >> 1) + 4 * (q & 1) + 8 * jj;
    const uint32_t d2 = tab + TD0 + 2 * (544 - p2);
    sts32(d2 - 4, __byte_perm(kv[2], 0, 0x1032));
    sts32(d2 + TD1, __byte_perm(kv[2], 0, 0x1010));
    sts16(d2, kv[2]); sts16(d2 + TD1 - 2, kv[2] >> 16);
    if (p2 != 256) { sts16(d2 + 2, kv[2]); sts16(d2 + TD1 + 4, kv[2]); }
    const uint32_t d3 = tab + TT2 + (q < 2 ? TT2SZ + 2 : 0) + 2 * (142 - 64 - 32 * (q & 1) - jj);
    sts16(d3, kv[3]); sts16(d3 - 32, kv[3] >> 16);
    uint32_t d4 = tab + TT3 + ((jj & 1) ? 0 : TT3SZ + 2) + 2 * (136 - 64 - 16 * q - (jj >> 1));
    sts16(d4 - 16, kv[4] >> 16); sts16(d4 - 16 + 194, kv[4] >> 16);
    if (tt == 0) {
        sts16(tab + TT2 + TT2SZ + 2 * (142 - 127), kv[4]);
        kv[4] = pack_f16(T.k2, 0.f); d4 = tab + TT3 + TT3SZ + 2 * (136 - 127);
    }
    sts16(d4, kv[4]); sts16(d4 + 194, kv[4]);
}

struct LnRows {
    uint32_t xb[28], piv[2];
#define LS(k, dep)
    __device__ __forceinline__ void load(const Params& P, int b, int at, uint32_t zero) {
        const __nv_bfloat16* xp = P.x + (b * 16 + (at >> 4)) * DM + zero;
        #pragma unroll
        for (int k = 0; k < 14; k++) ldg_v2(xp + (k % 7) * 64 + (k / 7) * 8 * DM + (at & 15) * 4, xb[2 * k], xb[2 * k + 1]);
        asm volatile("ld.global.nc.u16 %0, [%1];" : "=r"(piv[0]) : "l"(xp));
        asm volatile("ld.global.nc.u16 %0, [%1];" : "=r"(piv[1]) : "l"(xp + 8 * DM));
    }
    __device__ __forceinline__ void run(const Params& P, int b, int at, uint32_t lb, uint32_t tag) {
        float s1[2], s2[2];
        #pragma unroll
        for (int it = 0; it < 2; it++) {
            asm volatile("" : "+r"(piv[it]));
            const float pv = __uint_as_float(piv[it] << 16);
            s1[it] = 0.f; s2[it] = 0.f;
            #pragma unroll
            for (int k = 0; k < 14; k++) {
                asm volatile("" : "+r"(xb[14 * it + k]));
                const float a = bf_lo(xb[14 * it + k]) - pv, c = bf_hi(xb[14 * it + k]) - pv;
                s1[it] += a + c; s2[it] = fmaf(a, a, fmaf(c, c, s2[it]));
            }
        }
        LS(0, s1[0] + s2[1]);
        #pragma unroll
        for (int o = 8; o > 0; o >>= 1) {
            #pragma unroll
            for (int it = 0; it < 2; it++) { s1[it] += __shfl_xor_sync(0xffffffffu, s1[it], o); s2[it] += __shfl_xor_sync(0xffffffffu, s2[it], o); }
        }
        LS(1, s1[0] + s2[1]);
        float mean[2], var[2], den[2], inv[2], mb[2];
        #pragma unroll
        for (int it = 0; it < 2; it++) {
            const float dm = s1[it] * (1.f / DM);
            mean[it] = dm + __uint_as_float(piv[it] << 16);
            var[it] = fmaxf(fmaf(-dm, dm, s2[it] * (1.f / DM)), 0.f);
            den[it] = rbf(sqrt_fast(rbf(rbf(var[it]) + 1e-5f))); inv[it] = rcp_fast(den[it]);
            const uint32_t m2 = pack_bf16(mean[it], mean[it]);
            mb[it] = bf_hi(m2);
            #pragma unroll
            for (int k = 0; k < 7; k++) {
                const uint32_t d0 = U32(__hsub2(B2(xb[14 * it + 2 * k]), B2(m2))), d1 = U32(__hsub2(B2(xb[14 * it + 2 * k + 1]), B2(m2)));
                asm volatile("st.shared.v2.u32 [%0], {%1,%2};" :: "r"(lb + (it * 8 + (at >> 4)) * 912 + k * 128 + (at & 15) * 8),
                             "r"(pack_f16(bf_lo(d0) * inv[it], bf_hi(d0) * inv[it])), "r"(pack_f16(bf_lo(d1) * inv[it], bf_hi(d1) * inv[it])) : "memory");
            }
        }
        {
            const bool o = at & 1;
            const float vr = o ? var[1] : var[0], dn = o ? den[1] : den[0], iv = o ? inv[1] : inv[0], mn = o ? mean[1] : mean[0], mr = o ? mb[1] : mb[0];
            const float den2 = rbf(sqrt_fast(rbf(rbf(vr * iv * iv) + 1e-5f)));
            const float ia = dn * den2, r = -fmaf(rbf((mn - mr) * iv), dn, mr);
            const float rh = rbf(r), ih = rbf(ia);
            if ((at & 14) == 0)
                st_relaxed_v4(P.S->stats + b * 16 + (at & 1) * 8 + (at >> 4),
                              make_uint4(pack_bf16(rh, r - rh), pack_bf16(rh, ih), pack_bf16(ia - ih, 0.f), (__float_as_uint(rcp_fast(ia)) & ~1u) | tag));
        }
        LS(2, s1[0]);
    }
};
__device__ __forceinline__ void ln_publish(const Params& P, int b, int at, uint32_t lb, uint32_t tag) {
    const int lane = at & 31, mi = lane >> 3, ri = lane & 7;
    const uint32_t la = lb + ((ri >> 1) * 4 + (ri & 1) + (mi & 1) * 2) * 912 + (mi >> 1) * 16 + (at >> 5) * 224;
    __half* dp = P.S->xnT + ((at >> 5) * 112 + (lane >> 2)) * LSEQ + b * 16 + ((lane & 3) ^ ((b >> 1) & 2)) * 4;
    #pragma unroll
    for (int i = 0; i < 7; i++) {
        uint32_t r0, r1, r2, r3;
        ldsm4t(la + i * 32, r0, r1, r2, r3);
        st_relaxed_v2(dp + i * 16 * LSEQ, (r0 & ~1u) | tag, r1);
        st_relaxed_v2(dp + (i * 16 + 8) * LSEQ, (r2 & ~1u) | tag, r3);
    }
    if (lane == 0) red_relaxed(P.S->hint + (8 + (at >> 5)) * 32);
}

__device__ __forceinline__ void fetch_x(const Params& P, int ch, uint32_t tb, int tt) {
    #pragma unroll
    for (int i = 0; i < 4; i++)
        asm volatile("cp.async.cg.shared.global [%0], [%1], 16;" :: "r"(tb + T_XP + 512 + tt * 16 + i * 1024), "l"(P.S->xnT + ch * LSEQ + (i * 64 + tt) * 8) : "memory");
}
__device__ __forceinline__ uint32_t swz(int u) { return (uint32_t)(u ^ ((u >> 3) & 1)) * 16; }
template <int NU, bool ALL>
__device__ __forceinline__ void box_units(uint32_t tb, int u) {
    uint32_t e[12 + 4 * NU], o[10 + 4 * NU], qq[10 + 4 * NU];
    #pragma unroll
    for (int i = ALL ? 0 : 1; i < 3 + NU; i++) {
        const uint4 v = lds128(tb + T_XP + swz(u + 29 + i));
        e[4 * i] = v.x; e[4 * i + 1] = v.y; e[4 * i + 2] = v.z; e[4 * i + 3] = v.w;
    }
    #pragma unroll
    for (int k = ALL ? 2 : 7; k < 10 + 4 * NU; k++) { o[k] = __byte_perm(e[k], e[k + 1], 0x5432); qq[k] = hadd2u(e[k], o[k]); }
    #pragma unroll
    for (int n = 0; n < NU; n++) {
        uint32_t r2o[4], r2e[4], r3o[4], r3e[4];
        #pragma unroll
        for (int pp = 0; pp < 4; pp++) {
            const int p = 4 * n + pp;
            const uint32_t d8 = hadd2u(qq[8 + p], qq[7 + p]);
            r2o[pp] = hadd2u(qq[10 + p], o[9 + p]);
            r2e[pp] = hadd2u(e[9 + p], d8);
            if (ALL) {
                r3o[pp] = hadd2u(hadd2u(qq[9 + p], o[6 + p]), d8);
                r3e[pp] = hadd2u(hadd2u(e[6 + p], hadd2u(qq[5 + p], qq[4 + p])), hadd2u(qq[3 + p], qq[2 + p]));
            }
        }
        sts128(tb + T_U2O + (16 + u + n) * 16, r2o[0], r2o[1], r2o[2], r2o[3]);
        sts128(tb + T_U2O + U2SZ + (16 + u + n) * 16, r2e[0], r2e[1], r2e[2], r2e[3]);
        if (ALL) {
            const uint32_t a = tb + T_U3O + swz(u + n);
            sts128(a, r3o[0], r3o[1], r3o[2], r3o[3]);
            sts128(a + U3SZ, r3e[0], r3e[1], r3e[2], r3e[3]);
            sts128(a + 2 * U3SZ, qq[10 + 4 * n], qq[11 + 4 * n], qq[12 + 4 * n], qq[13 + 4 * n]);
        }
    }
}
__device__ __forceinline__ void prep(const Params& P, int ch, uint32_t tb, int tt, int bar, uint32_t tag) {
    sts128(tb + (tt < 32 ? T_XP + tt * 16 : T_U2O + ((tt >> 4) & 1) * U2SZ + (tt & 15) * 16), 0, 0, 0, 0);
    #pragma unroll 1
    for (int it = 0; it < (1 << 16); it++) {
        asm volatile("cp.async.wait_all;" ::: "memory");
        __syncwarp();
        uint32_t m = 0;
        #pragma unroll
        for (int i = 0; i < 2; i++) {
            uint32_t r0, r1, r2, r3, r4, r5, r6, r7;
            ldsm4(tb + T_XP + 512 + tt * 16 + i * 2048, r0, r1, r2, r3);
            ldsm4(tb + T_XP + 1536 + tt * 16 + i * 2048, r4, r5, r6, r7);
            m |= (r0 ^ tag) | (r1 ^ tag) | (r2 ^ tag) | (r3 ^ tag) | (r4 ^ tag) | (r5 ^ tag) | (r6 ^ tag) | (r7 ^ tag);
        }
        if (!__any_sync(0xffffffffu, m & ~tt & 1u)) break;
        __nanosleep(100);
        fetch_x(P, ch, tb, tt);
    }
    bar_sync(bar, 64);
    #pragma unroll 1
    for (int u = 128 + tt; u <= 192; u += 64) box_units<1, false>(tb, u);
    box_units<2, true>(tb, 2 * tt);
    bar_sync(bar, 64);
}
__device__ __forceinline__ void convolve(const Params& P, bool MLP, int ch, uint32_t tb, int tt, int bar, uint32_t tag, float yscale, int cw, int ca, long long tl0, long long* dbg = nullptr) {
    const int lane = tt & 31, w = tt >> 5, g = lane >> 2, q = lane & 3;
    const uint32_t stg = tb + T_STG + w * STG_W;
    float acc[16][4];
    #pragma unroll
    for (int a = 0; a < 16; a++) { acc[a][0] = acc[a][1] = acc[a][2] = acc[a][3] = 0.f; }
    const int dl = g - 2 * q;
    int xu = 2 * (16 + 8 * (lane >> 4) + (lane & 7) - w) + ((lane >> 3) & 1);
    const uint32_t xa0 = tb + T_XP + swz(xu);
    const uint32_t ra0 = tb + T_TAB + ((g & 1) ? TD1 + 2 : TD0) + 2 * (544 - dl) - 32 * w;
    {
        uint32_t xa = xa0, ra = ra0;
        uint32_t A[4][4], F[2][4][2];
        #pragma unroll
        for (int i = 0; i < 4; i++) { A[i][0] = lds32(ra - i * 256); A[i][1] = lds32(ra - i * 256 - 16); A[i][2] = lds32(ra - i * 256 + 16); A[i][3] = lds32(ra - i * 256); }
        ldsm4(xa, F[0][0][0], F[0][0][1], F[0][2][0], F[0][2][1]);
        ldsm4(xa + 2048, F[0][1][0], F[0][1][1], F[0][3][0], F[0][3][1]);
        if (cw >= 0) bar_sync(cw, 128);
        #pragma unroll 1
        for (int it = 0; it < 4; it++) {
            TL(17 + it - (it == 3 ? 10 : 0));
            if (it == CHAIN_IT && ca >= 0) bar_arrive(ca, 128);
            ra -= 64; xu -= 4;
            const uint32_t xn = tb + T_XP + swz(xu);
            #pragma unroll
            for (int mb = 0; mb < 4; mb++) {
                const int c = mb & 1, m = 2 * mb;
                const uint32_t na = mb < 3 ? xa + (m + 2) * 256 : xn;
                ldsm4(na, F[c ^ 1][0][0], F[c ^ 1][0][1], F[c ^ 1][2][0], F[c ^ 1][2][1]);
                ldsm4(na + 2048, F[c ^ 1][1][0], F[c ^ 1][1][1], F[c ^ 1][3][0], F[c ^ 1][3][1]);
                if (mb < 3) {
                    #pragma unroll
                    for (int f = 0; f < 4; f++) {
                        const int mm = m + (f >> 1) + (f & 1) * 8;
                        #pragma unroll
                        for (int i = 0; i < 4; i++) if (mm + i < 16) mma_f16(acc[mm + i], A[i][0], A[i][1], A[i][2], A[i][3], F[c][f][0], F[c][f][1]);
                    }
                } else {
                    #pragma unroll
                    for (int i = 3; i >= 0; i--) {
                        #pragma unroll
                        for (int f = 0; f < 4; f++) {
                            const int mm = m + (f >> 1) + (f & 1) * 8;
                            if (mm + i < 16) mma_f16(acc[mm + i], A[i][0], A[i][1], A[i][2], A[i][3], F[c][f][0], F[c][f][1]);
                        }
                        A[i][0] = lds32(ra - i * 256); A[i][1] = lds32(ra - i * 256 - 16); A[i][2] = lds32(ra - i * 256 + 16); A[i][3] = lds32(ra - i * 256);
                    }
                }
            }
            xa = xn;
        }
    }
    TL(16);
    const uint32_t lo = ((lane >> 4) * 8 + (lane & 7)) * 32 + (((lane >> 3) ^ (lane >> 2)) & 1) * 16, va = tb + T_U3O + lo;
    {
        uint32_t tp[10], t3[8][2];
        const uint32_t ta = tb + T_TAB + TT2 + w * TT2SZ + 2 * (142 - 56 - 2 * (g - q));
        #pragma unroll
        for (int i = 0; i < 10; i++) tp[i] = lds32(ta - i * 16);
        const uint32_t t3a = tb + T_TAB + TT3 + w * TT3SZ + ((g & 1) ? 194 : 0) + 2 * (136 - 56 - dl);
        #pragma unroll
        for (int i = 0; i < 8; i++) { t3[i][0] = lds32(t3a - i * 16 - 16); t3[i][1] = lds32(t3a - i * 16); }
        const uint32_t ua = tb + T_U2O + w * U2SZ + (16 + (lane >> 4) * 8 + ((lane >> 3) & 1) + (lane & 7)) * 16;
        #pragma unroll
        for (int kk = -1; kk <= 5; kk++) {
            uint32_t a0, a1, a2, a3, c0, c1, c2, c3;
            ldsm4t(ua + kk * 256, a0, a1, a2, a3);
            if (kk < 5) ldsm4t(ua + (kk + 7) * 256, c0, c1, c2, c3);
            #pragma unroll
            for (int e = 4; e <= 8; e++) {
                mma_f16(acc[kk + e], a0, a1, a2, a3, tp[2 * (e - 4) + 1], tp[2 * (e - 4)]);
                if (kk < 5 && kk + 7 + e < 16) mma_f16(acc[kk + 7 + e], c0, c1, c2, c3, tp[2 * (e - 4) + 1], tp[2 * (e - 4)]);
            }
        }
        #pragma unroll
        for (int kk = 0; kk < 4; kk++) {
            uint32_t a0, a1, a2, a3;
            ldsm4t(va + w * U3SZ + kk * 512, a0, a1, a2, a3);
            #pragma unroll
            for (int a = 15; a >= 8 + 2 * kk; a--) mma_f16(acc[a], a0, a1, a2, a3, t3[a - 2 * kk - 8][0], t3[a - 2 * kk - 8][1]);
        }
    }
    if (w) {
        uint32_t kx = lds32(tb + T_TAB + TT2 + TT2SZ + 2 * (142 - 128));
        kx = dl == 0 ? kx >> 16 : (dl == 1 ? kx : 0u);
        #pragma unroll
        for (int kk = 0; kk < 4; kk++) {
            uint32_t a0, a1, a2, a3;
            ldsm4t(va + 2 * U3SZ + kk * 512, a0, a1, a2, a3);
            mma_f16(acc[8 + 2 * kk], a0, a1, a2, a3, kx, 0u);
            mma_f16(acc[9 + 2 * kk], a0, a1, a2, a3, 0u, kx);
        }
    } else {
        const uint32_t a0 = lds32(ra0 - 1024), a1 = lds32(ra0 - 1024 - 16), a2 = lds32(ra0 - 1024 + 16), a3 = lds32(ra0 - 1024);
        #pragma unroll
        for (int m = 0; m < 12; m += 2) {
            uint32_t f0, f1, f2, f3;
            ldsm4(xa0 + m * 256, f0, f1, f2, f3);
            mma_f16(acc[m + 4], a0, a1, a2, a3, f0, f1);
            mma_f16(acc[m + 5], a0, a1, a2, a3, f2, f3);
        }
    }
    if (MLP) bar_arrive(BAR_B, 384);
    if (dbg) { if (acc[15][0] + acc[3][1] != 123.f) *dbg += clock64(); }
    TL(12);
    if (w) {
        #pragma unroll
        for (int a = 0; a < 8; a++) {
            sts128(stg + a * 512 + lane * 16, __float_as_uint(acc[a][0]), __float_as_uint(acc[a][1]), __float_as_uint(acc[a][2]), __float_as_uint(acc[a][3]));
            acc[a][0] = acc[8 + a][0]; acc[a][1] = acc[8 + a][1]; acc[a][2] = acc[8 + a][2]; acc[a][3] = acc[8 + a][3];
        }
    } else {
        #pragma unroll
        for (int a = 8; a < 16; a++)
            sts128(stg + (a - 8) * 512 + lane * 16, __float_as_uint(acc[a][0]), __float_as_uint(acc[a][1]), __float_as_uint(acc[a][2]), __float_as_uint(acc[a][3]));
    }
    bar_sync(bar, 64);
    uint4 o[8];
    #pragma unroll
    for (int a = 0; a < 8; a++) o[a] = lds128(tb + T_STG + (w ^ 1) * STG_W + lane * 16 + a * 512);
    #pragma unroll
    for (int a = 0; a < 8; a++) {
        o[a].x = pack_bf16((__uint_as_float(o[a].x) + acc[a][0]) * yscale, (__uint_as_float(o[a].y) + acc[a][1]) * yscale);
        o[a].y = pack_bf16((__uint_as_float(o[a].z) + acc[a][2]) * yscale, (__uint_as_float(o[a].w) + acc[a][3]) * yscale);
    }
    #pragma unroll
    for (int i = 0; i < 4; i++) stsm4t(stg + 4096 + i * 512 + lo, o[2 * i].x, o[2 * i].y, o[2 * i + 1].x, o[2 * i + 1].y);
    __syncwarp();
    __nv_bfloat16* sp = P.S->sT + ch * LSEQ + w * 1024 + lane * 8;
    #pragma unroll
    for (int i = 0; i < 4; i++) { uint4 v = lds128(stg + 4096 + i * 512 + swz(lane)); v.x = (v.x & ~1u) | tag; st_relaxed_v4(sp + i * 256, v); }
    if (lane == 0) red_relaxed(P.S->hint + (1 + (ch >> 6)) * 32);
}

__global__ void __launch_bounds__(384, 1)
fused_kernel(const Params P, const __grid_constant__ Maps maps) {
    extern __shared__ unsigned char smem_raw[];
    const long long tl0 = 0;
    const int tid = threadIdx.x, warp = tid >> 5, lane = tid & 31, b = blockIdx.x;
    const bool is_mlp = b < NMLP;
    const int team = is_mlp ? (warp >> 1) & 1 : warp >> 1, tt = tid & 63;
    int ch = is_mlp ? 2 * b + team : 2 * NMLP + (b - NMLP) * 6 + team;
    KGen K; LnRows L;
    K.load(P, is_mlp ? (warp < 8 ? 2 * b + (warp >> 2) : min(CH_EXP + b, DM - 1)) : ch, lane * 8 + (is_mlp ? (warp & 2) * 2 : (warp & 1) * 4));
    const int uw = __shfl_sync(0xffffffffu, warp, 0);
    const bool consumer = is_mlp && uw < 8, do_ln = uw >= 8 && b < 128;
    uint32_t epoch = 0;
    if (lane == 0) epoch = ld_relaxed(P.S->cnt + b * 8);
    const uint32_t sb = (smem_u32(smem_raw) + 1023) & ~1023u;
    const int mt = b & 15, j = b >> 4;
    const uint32_t tb = sb + (is_mlp ? O_AUX : 0) + team * TEAM;
    uint32_t stg;
    if (consumer) {
        if (elect_one()) {
            mbar_init(sb + O_BAR + uw * 8, uw < 7 ? 3 : 2);
            mbar_init(sb + O_BAR + 64 + uw * 8, uw < 6 ? 2 : 1);
            asm volatile("fence.mbarrier_init.release.cluster;" ::: "memory");
        }
        __syncwarp();
        if (uw == 7) {
            const int f = lane + FT0, kc = (f * 43) >> 7, r3 = f - kc * 3, n2 = (f - 21) >> 1;
            int cn = j + 1 + n2; if (cn >= 7) cn -= 7;
            uint32_t grp = kc, moff = 0, c0 = kc * 64, c1 = mt * 128, c2 = 0;
            if (f >= 21) { grp = 7 + n2; c0 = j * 64; if (f < 35) { moff = 256; c0 = cn * 64; c1 = j * 256 + ((f - 21) & 1) * 128; } }
            else if (r3 != 0) { moff = 128; c0 = 0; c1 = kc * 64 + (r3 - 1) * 32; c2 = j * 4; }
            sts128(sb + O_FILL + lane * 32, sb + (f - ((f * 57) >> 9) * NS) * SLOT, sb + O_BAR + grp * 8, moff, c0);
            sts128(sb + O_FILL + lane * 32 + 16, c1, c2, 0, 0);
            if (lane < 16) sts32(sb + O_REL + lane * 4, 0);
        }
        bar_sync(BAR_INIT, 256);
        stg = uw < 6 ? sb + 6 * SLOT + uw * STG_W : sb + O_AUX + TEAM + (uw - 6) * STG_W;
    } else {
        if (do_ln && !is_mlp) L.load(P, b, tid & 127, 0);
        stg = tb + T_STG + (uw & 1) * STG_W;
    }
    auto release = [&](int grp, int f0, int n) {
        unsigned old = 0;
        if (lane == 0) asm volatile("atom.relaxed.cta.shared.inc.u32 %0, [%1], 7;" : "=r"(old) : "r"(sb + O_REL + grp * 4) : "memory");
        old = __shfl_sync(0xffffffffu, old, 0);
        if (old == 7 && lane < n && f0 + lane < NFILL) {
            const uint4 e0 = lds128(sb + O_FILL + (f0 - FT0 + lane) * 32), e1 = lds128(sb + O_FILL + (f0 - FT0 + lane) * 32 + 16);
            tma_fill(maps.m, e0.x, e0.y, e0.z, e0.w, e1.x, e1.y);
        }
        __syncwarp();
    };
    K.consts();
    if (consumer) {
        if (uw < 2 && elect_one()) {
            const uint32_t kz = uw * 64 + K.zero;
            tma_fill(maps.m, sb + uw * 3 * SLOT, sb + O_BAR + uw * 8, 0, kz, mt * 128, 0);
            tma_fill(maps.m, sb + (uw * 3 + 1) * SLOT, sb + O_BAR + uw * 8, 128, 0, kz, j * 4);
            tma_fill(maps.m, sb + (uw * 3 + 2) * SLOT, sb + O_BAR + uw * 8, 128, 0, kz + 32, j * 4);
        }
        if (uw == 2 && mt < 10 && elect_one())
            asm volatile("cp.async.bulk.prefetch.tensor.3d.L2.global [%0, {%1, %2, %3}];" :: "l"(&maps.m[1]), "r"(0), "r"(128 + mt * 32 + K.zero), "r"(j * 4) : "memory");
        __syncwarp();
    } else if (is_mlp) {
        L.load(P, b, tid & 127, K.zero);
    }
    TL(2);
    if (is_mlp && (uw & 1)) { K.lar.x = K.lar.y; K.aim.x = K.aim.y; K.cre.x = K.cre.y; K.cim.x = K.cim.y; }
    uint32_t tag = 0;
    #pragma unroll 1
    for (int ps = is_mlp ? 2 : 0; ps < 4; ps++) {
        if (do_ln && ps == (is_mlp ? 3 : 0)) {
            epoch = __shfl_sync(0xffffffffu, epoch, 0); tag = (epoch & 1) ^ 1;
            const uint32_t lb = sb + (is_mlp ? O_AUX : 6 * TEAM);
            L.run(P, b, tid & 127, lb, tag);
            bar_sync(BAR_D, 128);
            ln_publish(P, b, tid & 127, lb, tag);
            TL(1);
        }
        if (!is_mlp && ps == HELP_HOLD && uw >= 8) bar_sync(10, 256);
        K.pass(stg, lane);
        K.contract(stg, lane);
        TL(8 + ps);
    }
    if (!is_mlp && uw < 4) bar_arrive(10, 256);
    K.deposit(consumer ? sb + O_DEP + uw * DEPSZ : stg, lane, (tid & (is_mlp ? 127 : 63)) == 0);
    if (consumer) {
        asm volatile("fence.proxy.async.shared::cta;" ::: "memory");
        release(13, 6, 3);
    }
    epoch = __shfl_sync(0xffffffffu, epoch, 0) + 1;
    tag = epoch & 1;

    if (consumer) {
        const int g = lane >> 2, q = lane & 3, wg = uw >> 2;
        bar_sync(BAR_K, 384);
        uint32_t h[64];
        {
            float acc[128];
            uint32_t st = sb;
            #pragma unroll 1
            for (int s = 0; s < 7; s++) {
                if (s == 5 && wg == 1) bar_sync(BAR_PP, 256);
                mbar_wait(sb + O_BAR + s * 8, 0);
                TL(12 + s);
                const uint64_t da = make_desc(st + wg * 8192, 16, 1024), db = make_desc(st + SLOT, 4096, 1024);
                WG_FENCE();
                wgmma_n256(acc, da, db, s);
                wgmma_n256(acc, da + 2, db + 128, 1);
                wgmma_n256(acc, da + 4, db + 1024, 1);
                wgmma_n256(acc, da + 6, db + 1152, 1);
                WG_COMMIT();
                st += 3 * SLOT; if (st == sb + NS * SLOT) st = sb;
                if (s == 1 && uw == 0 && mt < 14 && elect_one())
                    asm volatile("cp.async.bulk.prefetch.tensor.3d.L2.global [%0, {%1, %2, %3}];" :: "l"(&maps.m[2]), "r"((mt >> 1) * 64), "r"(j * 256 + (mt & 1) * 128), "r"(0) : "memory");
                if (s > 0 && s < 5) { WG_WAIT(1); release(s - 1, 3 * s + 6, 3); }
            }
            if (wg == 0) bar_arrive(BAR_PP, 256);
            TL(20);
            bar_sync(BAR_A + wg * (BAR_A2 - BAR_A), 256);
            const uint32_t sa = sb + O_STATS + (uw * 16 + g) * 16;
            uint32_t e0 = lds32(sa + q * 4), e1 = lds32(sa + 128 + q * 4);
            if (q == 3) { e0 = 0; e1 = 0; }
            WG_FENCE();
            wgmma_n256_rs(acc, e0, e1, (uint64_t)(((sb + O_BEXT) & 0x3FFFF) >> 4) | ((uint64_t)(128 >> 4) << 32));
            WG_COMMIT();
            WG_WAIT(0);
            release(6, 21, 9);
            TL(3);
            reg_fence(acc);
            const float al0 = ldsf(sa + 12), al1 = ldsf(sa + 140);
            const float hf0 = 0.5f * al0, hf1 = 0.5f * al1;
            #pragma unroll
            for (int ii = 0; ii < 64; ii++) {
                const int i = (ii + 32) & 63;
                const float hf = (i & 1) ? hf1 : hf0;
                const float v0 = acc[2 * i] * hf, v1 = acc[2 * i + 1] * hf;
                const float t0 = tanh_fast(v0 * fmaf(v0 * v0, 0.2854192648f, 1.5957691216f)), t1 = tanh_fast(v1 * fmaf(v1 * v1, 0.2854192648f, 1.5957691216f));
                h[i] = pack_bf16(fmaf(v0, t0, v0), fmaf(v1, t1, v1));
            }
        }
        TL(4);
        bar_sync(BAR_B, 384);
        float accA[32], accB[32];
        uint32_t st = (uint32_t)make_desc(sb + 3 * SLOT, 4096, 1024);
        const uint32_t st_end = (uint32_t)make_desc(sb, 4096, 1024) + NS * (SLOT >> 4);
        auto next_slot = [&]() { const uint32_t d = st; st += SLOT >> 4; if (st == st_end) st -= NS * (SLOT >> 4); return d; };
        auto send = [&](float (&acc)[32], int n) {
            int dest = j + 1 + n; if (dest >= 7) dest -= 7;
            uint4* op = P.S->part + ((mt * 7 + dest) * 7 + j) * 1024 + tid * 4 - lane * 3;
            reg_fence(acc);
            #pragma unroll
            for (int v = 0; v < 4; v++)
                st_relaxed_v4(op + v * 32, make_uint4((pack_bf16(acc[8 * v], acc[8 * v + 1]) & ~1u) | tag, pack_bf16(acc[8 * v + 2], acc[8 * v + 3]),
                                                       pack_bf16(acc[8 * v + 4], acc[8 * v + 5]), pack_bf16(acc[8 * v + 6], acc[8 * v + 7])));
            if (lane == 0) asm volatile("st.relaxed.gpu.global.u32 [%0], %1;" :: "l"(P.S->pflag + (mt * 7 + dest) * 64 + n * 8 + uw), "r"(epoch) : "memory");
        };
        if (wg == 1) bar_arrive(BAR_PP, 256);
        #pragma unroll 1
        for (int n = 0; n < 6; n += 2) {
            mbar_wait(sb + O_BAR + (7 + n) * 8, 0);
            mbar_wait(sb + O_BAR + (8 + n) * 8, 0);
            const uint32_t d0 = next_slot(), d1 = next_slot(), d2 = next_slot(), d3 = next_slot();
            bar_sync(BAR_PP + wg, 256);
            WG_FENCE();
            wgmma_n64_rs<0>(accA, h[60], h[61], h[62], h[63], d1 + 7 * 128);
            wgmma_n64_rs<0>(accB, h[60], h[61], h[62], h[63], d3 + 7 * 128);
            #pragma unroll
            for (int k = 14; k >= 0; k--) {
                wgmma_n64_rs<1>(accA, h[4 * k], h[4 * k + 1], h[4 * k + 2], h[4 * k + 3], (k < 8 ? d0 : d1) + (k & 7) * 128);
                wgmma_n64_rs<1>(accB, h[4 * k], h[4 * k + 1], h[4 * k + 2], h[4 * k + 3], (k < 8 ? d2 : d3) + (k & 7) * 128);
                if (k == PP_K && (n < 4 || wg == 0)) bar_arrive(BAR_PP + (wg ^ 1), 256);
            }
            WG_COMMIT();
            WG_WAIT(0);
            send(accA, n);
            send(accB, n + 1);
            if (n < 4) release(7 + n, 30 + 2 * n, 4);
            if ((tid & 127) == 0) sts32(sb + O_REL + 56 + wg * 4, n + 2);
            TL(21 + n);
        }
        {
            mbar_wait(sb + O_BAR + 13 * 8, 0);
            const uint32_t d0 = next_slot(), d1 = next_slot();
            WG_FENCE();
            wgmma_n64_rs<0>(accA, h[60], h[61], h[62], h[63], d1 + 7 * 128);
            #pragma unroll
            for (int k = 14; k >= 0; k--)
                wgmma_n64_rs<1>(accA, h[4 * k], h[4 * k + 1], h[4 * k + 2], h[4 * k + 3], (k < 8 ? d0 : d1) + (k & 7) * 128);
            WG_COMMIT();
        }
        TL(7);
        bar_sync(BAR_C, 384);
        mbar_wait(sb + O_BAR + 14 * 8, 0);
        uint32_t sv[16], xv[16];
        uint4 sm[8];
        {
            const uint32_t sa = sb + O_AUX + ((lane >> 4) * 8 + (lane & 7)) * 272 + (warp * 16 + ((lane >> 3) & 1) * 8) * 2;
            const int xr = warp * 16 + (lane & 15);
            const uint32_t xa = sb + (35 % NS) * SLOT + xr * 128;
            #pragma unroll
            for (int i = 0; i < 4; i++) {
                ldsm4t(sa + i * 16 * 272, sv[4 * i], sv[4 * i + 1], sv[4 * i + 2], sv[4 * i + 3]);
                ldsm4(xa + (((2 * i + (lane >> 4)) ^ (xr & 7)) << 4), xv[4 * i], xv[4 * i + 1], xv[4 * i + 2], xv[4 * i + 3]);
            }
            #pragma unroll
            for (int i = 0; i < 8; i++) sm[i] = lds128(sb + O_SUM + warp * 4096 + i * 512 + lane * 16);
        }
        WG_WAIT(0);
        reg_fence(accA);
        TL(8);
        #pragma unroll
        for (int i = 0; i < 16; i++) {
            const float h0 = fmaf(0.5f, accA[2 * i], __uint_as_float((i & 1) ? sm[i >> 1].z : sm[i >> 1].x));
            const float h1 = fmaf(0.5f, accA[2 * i + 1], __uint_as_float((i & 1) ? sm[i >> 1].w : sm[i >> 1].y));
            const uint32_t g2 = pack_bf16(fmaf(h0, tanh_fast(h0), h0), fmaf(h1, tanh_fast(h1), h1));
            xv[i] = U32(__hadd2(B2(xv[i]), __hmul2(B2(sv[i]), B2(g2))));
        }
        const uint32_t ob = sb + O_SUM + warp * 4096;
        __syncwarp();
        #pragma unroll
        for (int i = 0; i < 4; i++) stsm4(ob + (lane & 15) * 144 + (2 * i + (lane >> 4)) * 16, xv[4 * i], xv[4 * i + 1], xv[4 * i + 2], xv[4 * i + 3]);
        __syncwarp();
        __nv_bfloat16* op = P.out + (size_t)(mt * 128 + warp * 16 + (lane >> 3)) * DM + j * 64 + (lane & 7) * 8;
        #pragma unroll
        for (int i = 0; i < 4; i++) *reinterpret_cast<uint4*>(op + i * 4 * DM) = lds128(ob + (i * 4 + (lane >> 3)) * 144 + (lane & 7) * 16);
        TL(9);
    } else {
        const int at = tid - 256;
        Taps T;
        if (is_mlp) bar_sync(BAR_K, 384);
        #pragma unroll 1
        for (int i = tt; i < TABSZ / 16; i += 64) sts128(tb + T_TAB + i * 16, 0, 0, 0, 0);
        if (is_mlp) {
            uint32_t wv[28];
            {
                const __nv_bfloat16* wp = P.w1 + ((b & 3) * 112 + (at >> 4)) * FF + (b >> 2) * 64 + (at & 15) * 4;
                #pragma unroll
                for (int r = 0; r < 14; r++) ldg_v2(wp + r * 8 * FF, wv[2 * r], wv[2 * r + 1]);
            }
            if (at == 0) P.S->cnt[b * 8] = epoch;
            TL(3);
            if (team == 1 && CH_EXP + b < DM) {
                T = sum_deposits<4>(sb + O_AUX + T_STG, STG_W, TEAM, tt);
                st_relaxed_v4(P.S->kexp + b * 128 + tt, make_uint4(T.kv[0], T.kv[1], T.kv[2], (__float_as_uint(T.k2) & ~1u) | tag));
                st_relaxed_v4(P.S->kexp + b * 128 + 64 + tt, make_uint4(T.kv[3], T.kv[4], __float_as_uint(T.yscale), tag));
            }
            T = sum_deposits<4>(sb + O_DEP + team * 4 * DEPSZ, DEPSZ, 2 * DEPSZ, tt);
            float c[4] = {0.f, 0.f, 0.f, 0.f};
            #pragma unroll
            for (int r = 0; r < 28; r++) { c[(r & 1) * 2] += bf_lo(wv[r]); c[(r & 1) * 2 + 1] += bf_hi(wv[r]); }
            #pragma unroll
            for (int i = 0; i < 4; i++) c[i] += __shfl_xor_sync(0xffffffffu, c[i], 16);
            if (lane < 16) sts128(sb + O_CSS + (at >> 5) * 256 + lane * 16, __float_as_uint(c[0]), __float_as_uint(c[1]), __float_as_uint(c[2]), __float_as_uint(c[3]));
            bar_sync(BAR_AUX, 128);
            if (at < 64) {
                const float t = (ldsf(sb + O_CSS + at * 4) + ldsf(sb + O_CSS + 256 + at * 4)) + (ldsf(sb + O_CSS + 512 + at * 4) + ldsf(sb + O_CSS + 768 + at * 4));
                asm volatile("st.relaxed.gpu.global.u32 [%0], %1;" :: "l"(P.S->cs + ((b >> 2) * 64 + at) * 4 + (b & 3)), "r"((__float_as_uint(t) & ~1u) | tag) : "memory");
            }
            TL(6);
        } else {
            bar_sync(1 + team, 64);
            T = sum_deposits<2>(tb + T_STG, STG_W, 0, tt);
        }
        if (tt < 32) wait_hint(P.S->hint + (8 + ch / 112) * 32, epoch * 128);
        bar_sync(1 + team, 64);
        fetch_x(P, ch, tb, tt);
        TL(31);
        #pragma unroll 1
        for (;;) {
            int tq = tt; uint32_t tbq = tb; asm volatile("" : "+r"(tq), "+r"(tbq));
            scatter_taps(T, tbq, tq);
            TL(4);
            if (is_mlp) {
                const uint32_t bb = __ldg(reinterpret_cast<const uint32_t*>(P.b1 + j * 256 + at * 2));
                uint4 st, c0, c1;
                #pragma unroll 1
                for (int it = 0; it < (1 << 16); it++) {
                    st = ld_relaxed_v4(P.S->stats + mt * 128 + at);
                    c0 = ld_relaxed_4x32(P.S->cs + (j * 256 + at * 2) * 4); c1 = ld_relaxed_4x32(P.S->cs + (j * 256 + at * 2) * 4 + 4);
                    if (!__any_sync(0xffffffffu, ((st.w ^ tag) | (c0.x ^ tag) | (c0.y ^ tag) | (c0.z ^ tag) | (c0.w ^ tag) | (c1.x ^ tag) | (c1.y ^ tag) | (c1.z ^ tag) | (c1.w ^ tag)) & 1u)) break;
                    __nanosleep(100);
                }
                sts128(sb + O_STATS + at * 16, st.x, st.y, st.z, st.w);
                const float cx = (__uint_as_float(c0.x) + __uint_as_float(c0.y)) + (__uint_as_float(c0.z) + __uint_as_float(c0.w));
                const float cy = (__uint_as_float(c1.x) + __uint_as_float(c1.y)) + (__uint_as_float(c1.z) + __uint_as_float(c1.w));
                const uint32_t ch2 = pack_bf16(cx, cy), cl2 = pack_bf16(cx - bf_lo(ch2), cy - bf_hi(ch2));
                sts128(sb + O_BEXT + at * 32, __byte_perm(ch2, 0, 0x1010), __byte_perm(cl2, bb, 0x5410), bb & 0xffffu, 0);
                sts128(sb + O_BEXT + at * 32 + 16, __byte_perm(ch2, 0, 0x3232), __byte_perm(cl2, bb, 0x7632), bb >> 16, 0);
                asm volatile("fence.proxy.async.shared::cta;" ::: "memory");
                bar_arrive(BAR_A, 256); bar_arrive(BAR_A2, 256);
                TL(5);
            }
            prep(P, ch, tbq, tq, 1 + team, tag);
            TL(7);
            const int cb = (team & 1) ? 13 : 7, gi = team >> 1, nxt = gi == 2 ? ch + NHELP * 6 - 4 : ch + 2;
            convolve(P, is_mlp, ch, tbq, tq, 1 + team, tag, T.yscale,
                     (is_mlp || (gi == 0 && ch < CH_EXP)) ? -1 : cb + gi, (is_mlp || nxt >= DM) ? -1 : cb + (gi == 2 ? 0 : gi + 1), tl0);
            TL(13);
            ch += NHELP * 6;
            if (is_mlp || ch >= DM) break;
            uint4 e0, e1;
            #pragma unroll 1
            for (int it = 0; it < (1 << 16); it++) {
                e0 = ld_relaxed_v4(P.S->kexp + (ch - CH_EXP) * 128 + tq); e1 = ld_relaxed_v4(P.S->kexp + (ch - CH_EXP) * 128 + 64 + tq);
                if (it == 0) { bar_sync(1 + team, 64); fetch_x(P, ch, tbq, tq); }
                if (!__any_sync(0xffffffffu, ((e0.w ^ tag) | (e1.w ^ tag)) & 1u)) break;
            }
            T.kv[0] = e0.x; T.kv[1] = e0.y; T.kv[2] = e0.z; T.kv[3] = e1.x; T.kv[4] = e1.y;
            T.k2 = __uint_as_float(e0.w); T.yscale = __uint_as_float(e1.z);
        }
        if (!is_mlp) { if (tid == 0) P.S->cnt[b * 8] = epoch; return; }
        uint32_t b2v[8];
        #pragma unroll
        for (int i = 0; i < 8; i++) b2v[i] = __ldg(reinterpret_cast<const uint32_t*>(P.b2 + j * 64 + (at & 3) * 2 + i * 8));
        float sum[64];
        #pragma unroll
        for (int i = 0; i < 64; i++) sum[i] = 0.f;
        bar_sync(BAR_AUX, 128);
        #pragma unroll 1
        for (int step = 0; step < 6; step += 2) {
            if (step == 4) {
                wait_hint(P.S->hint + (1 + j) * 32, epoch * 128);
                uint4 sv[8];
                #pragma unroll 1
                for (int it = 0; it < (1 << 16); it++) {
                    uint32_t m = 0;
                    #pragma unroll
                    for (int v = 0; v < 8; v++) { sv[v] = ld_relaxed_v4(P.S->sT + (j * 64 + v * 8 + (at >> 4)) * LSEQ + mt * 128 + (at & 15) * 8); m |= sv[v].x ^ tag; }
                    if (!__any_sync(0xffffffffu, m & 1u)) break;
                }
                #pragma unroll
                for (int v = 0; v < 8; v++) sts128(sb + O_AUX + (v * 8 + (at >> 4)) * 272 + (at & 15) * 16, sv[v].x, sv[v].y, sv[v].z, sv[v].w);
                TL(20);
            }
            int s0 = j - 1 - step, s1 = s0 - 1; if (s0 < 0) s0 += 7; if (s1 < 0) s1 += 7;
            const uint4* ib = P.S->part + (mt * 7 + j) * 7 * 1024 + at * 8 - (at & 31) * 7;
            #pragma unroll 1
            for (int it = 0; it < (1 << 16); it++) {
                if ((int)lds32(sb + O_REL + 56 + (at >> 6) * 4) > step) break;
                __nanosleep(64);
            }
            #pragma unroll 1
            for (int it = 0; it < (1 << 16); it++) {
                const unsigned f = ld_relaxed(P.S->pflag + (mt * 7 + j) * 64 + (step + ((lane >> 1) & 1)) * 8 + (at >> 5) * 2 + (lane & 1));
                if (__all_sync(0xffffffffu, f == epoch)) break;
                __nanosleep(50);
            }
            uint4 pv[16];
            #pragma unroll 1
            for (int it = 0; it < (1 << 16); it++) {
                uint32_t m = 0;
                #pragma unroll
                for (int v = 0; v < 16; v++) { pv[v] = ld_relaxed_v4(ib + (v < 8 ? s0 : s1) * 1024 + (v & 7) * 32); m |= pv[v].x ^ tag; }
                if (!__any_sync(0xffffffffu, m & 1u)) break;
                __nanosleep(100);
            }
            #pragma unroll
            for (int v = 0; v < 8; v++) {
                sum[8 * v + 0] += bf_lo(pv[v].x) + bf_lo(pv[v + 8].x); sum[8 * v + 1] += bf_hi(pv[v].x) + bf_hi(pv[v + 8].x);
                sum[8 * v + 2] += bf_lo(pv[v].y) + bf_lo(pv[v + 8].y); sum[8 * v + 3] += bf_hi(pv[v].y) + bf_hi(pv[v + 8].y);
                sum[8 * v + 4] += bf_lo(pv[v].z) + bf_lo(pv[v + 8].z); sum[8 * v + 5] += bf_hi(pv[v].z) + bf_hi(pv[v + 8].z);
                sum[8 * v + 6] += bf_lo(pv[v].w) + bf_lo(pv[v + 8].w); sum[8 * v + 7] += bf_hi(pv[v].w) + bf_hi(pv[v + 8].w);
            }
            TL(21 + step);
        }
        #pragma unroll
        for (int i = 0; i < 16; i++)
            sts128(sb + O_SUM + (at >> 5) * 8192 + i * 512 + (at & 31) * 16,
                   __float_as_uint(0.5f * (sum[4 * i] + bf_lo(b2v[i & 7]))), __float_as_uint(0.5f * (sum[4 * i + 1] + bf_hi(b2v[i & 7]))),
                   __float_as_uint(0.5f * (sum[4 * i + 2] + bf_lo(b2v[i & 7]))), __float_as_uint(0.5f * (sum[4 * i + 3] + bf_hi(b2v[i & 7]))));
        bar_arrive(BAR_C, 384);
    }
}

typedef CUresult (*EncodeFn)(CUtensorMap*, CUtensorMapDataType, cuuint32_t, void*, const cuuint64_t*, const cuuint64_t*, const cuuint32_t*,
                             const cuuint32_t*, CUtensorMapInterleave, CUtensorMapSwizzle, CUtensorMapL2promotion, CUtensorMapFloatOOBfill);

}

extern "C" void kernel_launch(void* const* d_in, const int* in_sizes, int n_in, void* d_out, int out_size) {
    (void)in_sizes; (void)n_in; (void)out_size;
    static EncodeFn enc = nullptr;
    static Scratch* scr = nullptr;
    if (!enc) {
        void* fn = nullptr; cudaDriverEntryPointQueryResult qr;
        cudaGetDriverEntryPoint("cuTensorMapEncodeTiled", &fn, cudaEnableDefault, &qr);
        enc = (EncodeFn)fn;
        cudaGetSymbolAddress((void**)&scr, g_scr);
        cudaFuncSetAttribute(fused_kernel, cudaFuncAttributeMaxDynamicSharedMemorySize, SMEM_BYTES);
    }
    Maps maps;
    const cuuint32_t es[3] = {1, 1, 1};
    { cuuint64_t gd[3] = {DM, LSEQ, 1}; cuuint64_t gs[2] = {DM * 2, (cuuint64_t)DM * 2 * LSEQ}; cuuint32_t bd[3] = {64, 128, 1};
      enc(&maps.m[0], CU_TENSOR_MAP_DATA_TYPE_BFLOAT16, 3, d_in[0], gd, gs, bd, es, CU_TENSOR_MAP_INTERLEAVE_NONE, CU_TENSOR_MAP_SWIZZLE_128B, CU_TENSOR_MAP_L2_PROMOTION_L2_128B, CU_TENSOR_MAP_FLOAT_OOB_FILL_NONE); }
    { cuuint64_t gd[3] = {64, DM, FF / 64}; cuuint64_t gs[2] = {FF * 2, 128}; cuuint32_t bd[3] = {64, 32, 4};
      enc(&maps.m[1], CU_TENSOR_MAP_DATA_TYPE_BFLOAT16, 3, d_in[8], gd, gs, bd, es, CU_TENSOR_MAP_INTERLEAVE_NONE, CU_TENSOR_MAP_SWIZZLE_128B, CU_TENSOR_MAP_L2_PROMOTION_L2_128B, CU_TENSOR_MAP_FLOAT_OOB_FILL_NONE); }
    { cuuint64_t gd[3] = {DM, FF, 1}; cuuint64_t gs[2] = {DM * 2, (cuuint64_t)DM * 2 * FF}; cuuint32_t bd[3] = {64, 128, 1};
      enc(&maps.m[2], CU_TENSOR_MAP_DATA_TYPE_BFLOAT16, 3, d_in[10], gd, gs, bd, es, CU_TENSOR_MAP_INTERLEAVE_NONE, CU_TENSOR_MAP_SWIZZLE_128B, CU_TENSOR_MAP_L2_PROMOTION_L2_128B, CU_TENSOR_MAP_FLOAT_OOB_FILL_NONE); }
    Params P;
    P.x = (const __nv_bfloat16*)d_in[0]; P.lar = (const __nv_bfloat16*)d_in[1]; P.aim = (const __nv_bfloat16*)d_in[2];
    P.cre = (const __nv_bfloat16*)d_in[3]; P.cim = (const __nv_bfloat16*)d_in[4]; P.ldt = (const __nv_bfloat16*)d_in[5];
    P.dsk = (const __nv_bfloat16*)d_in[6]; P.w1 = (const __nv_bfloat16*)d_in[8]; P.b1 = (const __nv_bfloat16*)d_in[9];
    P.b2 = (const __nv_bfloat16*)d_in[11]; P.out = (__nv_bfloat16*)d_out; P.S = scr;
    fused_kernel<<<NCTA, 384, SMEM_BYTES, cudaStreamPerThread>>>(P, maps);
}
```

```cpp
#include <cuda_runtime.h>
#include <cuda.h>
#include <cuda_bf16.h>
#include <cuda_fp16.h>
#include <stdint.h>

#define FORCE_FALLBACK 0

namespace {

constexpr int LSEQ = 2048, DM = 448, NMODE = 256, FF = 1792;
constexpr int NMLP = 112, NHELP = 20, NCTA = NMLP + NHELP;
constexpr int CH_EXP = 2 * NMLP + 6 * NHELP;
constexpr int FT0 = 6, DEPSZ = 1296;
constexpr int NS = 9, SLOT = 16384, NFILL = 35;
constexpr int T_XP = 0;
constexpr int T_U2O = 4608, U2SZ = 3360;
constexpr int T_U3O = T_U2O + 2 * U2SZ, U3SZ = 2048;
constexpr int T_STG = T_U3O + 3 * U3SZ;
constexpr int STG_W = 7168;
constexpr int T_TAB = T_STG + 2 * STG_W;
constexpr int TD0 = 0, TD1 = 1216;
constexpr int TT2 = 2368, TT2SZ = 192;
constexpr int TT3 = TT2 + 2 * TT2SZ, TT3SZ = 384;
constexpr int TABSZ = TT3 + 2 * TT3SZ;
constexpr int TEAM = T_TAB + TABSZ + 64;
constexpr int O_AUX = NS * SLOT;
constexpr int O_SUM = O_AUX + 17408;
constexpr int O_BEXT = O_AUX + 2 * TEAM;
constexpr int O_STATS = O_BEXT + 4096;
constexpr int O_B2 = O_STATS + 2048;
constexpr int O_DEP = O_BEXT;
constexpr int O_CSS = O_DEP + 8 * DEPSZ;
constexpr int O_FILL = O_CSS + 1024;
constexpr int O_BAR = O_FILL + 1024;
constexpr int O_REL = O_BAR + 128;
constexpr int SMEM_USED = O_REL + 64;
constexpr int SMEM_BYTES = SMEM_USED + 1024;
static_assert(SMEM_BYTES <= 232448, "smem");
static_assert(6 * TEAM + 16 * 912 <= SMEM_USED, "helper smem");
static_assert(TEAM % 16 == 0 && O_BEXT % 128 == 0 && O_CSS % 16 == 0, "align");

enum { BAR_PP = 5, BAR_AUX = 7, BAR_A = 8, BAR_C = 10, BAR_INIT = 11, BAR_D = 12, BAR_A2 = 15 };

struct alignas(1024) Scratch {
    unsigned cnt[NCTA * 8];
    unsigned hint[12 * 32];
    unsigned cs[FF * 4];
    uint4 stats[LSEQ];
    uint4 kexp[NMLP * 128];
    unsigned pflag[16 * 7 * 64];
    __half xnT[DM * LSEQ];
    __nv_bfloat16 sT[DM * LSEQ];
    uint4 part[16 * 7 * 7 * 1024];
};
__device__ Scratch g_scr;

struct Params {
    const __nv_bfloat16 *x, *lar, *aim, *cre, *cim, *ldt, *dsk, *w1, *b1, *b2;
    __nv_bfloat16* out;
    Scratch* S;
};

__device__ __forceinline__ uint32_t smem_u32(const void* p) { return (uint32_t)__cvta_generic_to_shared(p); }
__device__ __forceinline__ void mbar_init(uint32_t bar, uint32_t cnt) { asm volatile("mbarrier.init.shared::cta.b64 [%0], %1;" :: "r"(bar), "r"(cnt)); }
__device__ __forceinline__ void mbar_expect_tx(uint32_t bar, uint32_t bytes) { asm volatile("mbarrier.arrive.expect_tx.shared::cta.b64 _, [%0], %1;" :: "r"(bar), "r"(bytes) : "memory"); }
__device__ __forceinline__ void mbar_arrive(uint32_t bar) { asm volatile("mbarrier.arrive.shared::cta.b64 _, [%0];" :: "r"(bar) : "memory"); }
__device__ __forceinline__ bool mbar_test(uint32_t bar, uint32_t parity) {
    uint32_t ok;
    asm volatile("{\n.reg .pred p;\nmbarrier.test_wait.parity.shared::cta.b64 p, [%1], %2;\nselp.u32 %0, 1, 0, p;\n}" : "=r"(ok) : "r"(bar), "r"(parity) : "memory");
    return ok;
}
__device__ __forceinline__ void mbar_wait(uint32_t bar, uint32_t parity) {
    #pragma unroll 1
    for (int i = 0; i < (1 << 16); i++) {
        uint32_t ok;
        asm volatile("{\n.reg .pred p;\nmbarrier.try_wait.parity.shared::cta.b64 p, [%1], %2;\nselp.u32 %0, 1, 0, p;\n}" : "=r"(ok) : "r"(bar), "r"(parity) : "memory");
        if (ok) return;
    }
}
__device__ __forceinline__ void bar_sync(int id, int n) { asm volatile("bar.sync %0, %1;" :: "r"(id), "r"(n) : "memory"); }
__device__ __forceinline__ void bar_arrive(int id, int n) { asm volatile("bar.arrive %0, %1;" :: "r"(id), "r"(n) : "memory"); }
__device__ __forceinline__ unsigned ld_relaxed(const unsigned* p) { unsigned v; asm volatile("ld.relaxed.gpu.global.u32 %0, [%1];" : "=r"(v) : "l"(p) : "memory"); return v; }
__device__ __forceinline__ void red_relaxed(unsigned* p) { asm volatile("red.relaxed.gpu.global.add.u32 [%0], 1;" :: "l"(p) : "memory"); }
__device__ __forceinline__ void wait_hint(const unsigned* p, unsigned target) {
    if ((threadIdx.x & 31) == 0) {
        #pragma unroll 1
        for (int i = 0; i < (1 << 16); i++) { if ((int)(ld_relaxed(p) - target) >= 0) break; __nanosleep(50); }
    }
    __syncwarp();
}
__device__ __forceinline__ uint4 ld_relaxed_v4(const void* p) {
    uint4 v;
    asm volatile("{\n.reg .b128 t;\nld.relaxed.gpu.global.b128 t, [%4];\nmov.b128 {%0,%1,%2,%3}, t;\n}" : "=r"(v.x), "=r"(v.y), "=r"(v.z), "=r"(v.w) : "l"(p) : "memory");
    return v;
}
__device__ __forceinline__ void st_relaxed_v4(void* p, uint4 v) {
    asm volatile("{\n.reg .b128 t;\nmov.b128 t, {%1,%2,%3,%4};\nst.relaxed.gpu.global.b128 [%0], t;\n}" :: "l"(p), "r"(v.x), "r"(v.y), "r"(v.z), "r"(v.w) : "memory");
}
__device__ __forceinline__ void st_relaxed_v2(void* p, uint32_t x, uint32_t y) {
    asm volatile("{\n.reg .b64 t;\nmov.b64 t, {%1,%2};\nst.relaxed.gpu.global.b64 [%0], t;\n}" :: "l"(p), "r"(x), "r"(y) : "memory");
}
__device__ __forceinline__ uint4 ld_relaxed_4x32(const void* p) {
    uint4 v; asm volatile("ld.relaxed.gpu.global.v4.u32 {%0,%1,%2,%3}, [%4];" : "=r"(v.x), "=r"(v.y), "=r"(v.z), "=r"(v.w) : "l"(p) : "memory"); return v;
}
__device__ __forceinline__ uint4 lds128(uint32_t a) { uint4 v; asm volatile("ld.shared.v4.u32 {%0,%1,%2,%3}, [%4];" : "=r"(v.x), "=r"(v.y), "=r"(v.z), "=r"(v.w) : "r"(a) : "memory"); return v; }
__device__ __forceinline__ uint32_t lds32(uint32_t a) { uint32_t v; asm volatile("ld.shared.u32 %0, [%1];" : "=r"(v) : "r"(a) : "memory"); return v; }
__device__ __forceinline__ float ldsf(uint32_t a) { return __uint_as_float(lds32(a)); }
__device__ __forceinline__ void sts128(uint32_t a, uint32_t x, uint32_t y, uint32_t z, uint32_t w) { asm volatile("st.shared.v4.u32 [%0], {%1,%2,%3,%4};" :: "r"(a), "r"(x), "r"(y), "r"(z), "r"(w) : "memory"); }
__device__ __forceinline__ void sts32(uint32_t a, uint32_t x) { asm volatile("st.shared.u32 [%0], %1;" :: "r"(a), "r"(x) : "memory"); }
__device__ __forceinline__ void ldsm4(uint32_t a, uint32_t& r0, uint32_t& r1, uint32_t& r2, uint32_t& r3) {
    asm volatile("ldmatrix.sync.aligned.m8n8.x4.shared.b16 {%0,%1,%2,%3}, [%4];" : "=r"(r0), "=r"(r1), "=r"(r2), "=r"(r3) : "r"(a) : "memory");
}
__device__ __forceinline__ void ldsm4t(uint32_t a, uint32_t& r0, uint32_t& r1, uint32_t& r2, uint32_t& r3) {
    asm volatile("ldmatrix.sync.aligned.m8n8.x4.trans.shared.b16 {%0,%1,%2,%3}, [%4];" : "=r"(r0), "=r"(r1), "=r"(r2), "=r"(r3) : "r"(a) : "memory");
}
__device__ __forceinline__ void ldsm2t(uint32_t a, uint32_t& r0, uint32_t& r1) {
    asm volatile("ldmatrix.sync.aligned.m8n8.x2.trans.shared.b16 {%0,%1}, [%2];" : "=r"(r0), "=r"(r1) : "r"(a) : "memory");
}
__device__ __forceinline__ void stsm4(uint32_t a, uint32_t r0, uint32_t r1, uint32_t r2, uint32_t r3) {
    asm volatile("stmatrix.sync.aligned.m8n8.x4.shared.b16 [%0], {%1,%2,%3,%4};" :: "r"(a), "r"(r0), "r"(r1), "r"(r2), "r"(r3) : "memory");
}
__device__ __forceinline__ void stsm4t(uint32_t a, uint32_t r0, uint32_t r1, uint32_t r2, uint32_t r3) {
    asm volatile("stmatrix.sync.aligned.m8n8.x4.trans.shared.b16 [%0], {%1,%2,%3,%4};" :: "r"(a), "r"(r0), "r"(r1), "r"(r2), "r"(r3) : "memory");
}
__device__ __forceinline__ void mma_f16(float (&c)[4], uint32_t a0, uint32_t a1, uint32_t a2, uint32_t a3, uint32_t b0, uint32_t b1) {
    asm volatile("mma.sync.aligned.m16n8k16.row.col.f32.f16.f16.f32 {%0,%1,%2,%3}, {%4,%5,%6,%7}, {%8,%9}, {%0,%1,%2,%3};"
        : "+f"(c[0]), "+f"(c[1]), "+f"(c[2]), "+f"(c[3]) : "r"(a0), "r"(a1), "r"(a2), "r"(a3), "r"(b0), "r"(b1));
}
__device__ __forceinline__ void mma_bf16(float* c, uint32_t a0, uint32_t a1, uint32_t a2, uint32_t a3, uint32_t b) {
    asm volatile("mma.sync.aligned.m16n8k16.row.col.f32.bf16.bf16.f32 {%0,%1,%2,%3}, {%4,%5,%6,%7}, {%8,%8}, {%0,%1,%2,%3};"
        : "+f"(c[0]), "+f"(c[1]), "+f"(c[2]), "+f"(c[3]) : "r"(a0), "r"(a1), "r"(a2), "r"(a3), "r"(b));
}
__device__ __forceinline__ uint32_t pack_bf16(float lo, float hi) { uint32_t r; asm("cvt.rn.bf16x2.f32 %0, %1, %2;" : "=r"(r) : "f"(hi), "f"(lo)); return r; }
__device__ __forceinline__ uint32_t pack_f16(float lo, float hi) { uint32_t r; asm("cvt.rn.f16x2.f32 %0, %1, %2;" : "=r"(r) : "f"(hi), "f"(lo)); return r; }
__device__ __forceinline__ float bf_lo(uint32_t v) { return __uint_as_float(v << 16); }
__device__ __forceinline__ float bf_hi(uint32_t v) { return __uint_as_float(v & 0xffff0000u); }
__device__ __forceinline__ float rbf(float v) { return __uint_as_float(pack_bf16(0.f, v)); }
__device__ __forceinline__ float tanh_fast(float v) { float r; asm("tanh.approx.f32 %0, %1;" : "=f"(r) : "f"(v)); return r; }
__device__ __forceinline__ float ex2_fast(float v) { float r; asm("ex2.approx.ftz.f32 %0, %1;" : "=f"(r) : "f"(v)); return r; }
__device__ __forceinline__ __half2 H2(uint32_t v) { return *reinterpret_cast<__half2*>(&v); }
__device__ __forceinline__ uint32_t U32(__half2 v) { return *reinterpret_cast<uint32_t*>(&v); }
__device__ __forceinline__ __nv_bfloat162 B2(uint32_t v) { return *reinterpret_cast<__nv_bfloat162*>(&v); }
__device__ __forceinline__ uint32_t U32(__nv_bfloat162 v) { return *reinterpret_cast<uint32_t*>(&v); }
__device__ __forceinline__ uint32_t hadd2u(uint32_t a, uint32_t b) { return U32(__hadd2(H2(a), H2(b))); }

__device__ __forceinline__ uint64_t make_desc(uint32_t addr, uint32_t lbo, uint32_t sbo) {
    return (uint64_t)((addr & 0x3FFFF) >> 4) | ((uint64_t)(lbo >> 4) << 16) | ((uint64_t)(sbo >> 4) << 32) | ((uint64_t)1 << 62);
}
#define ACC8(d, b) "+f"(d[b+0]), "+f"(d[b+1]), "+f"(d[b+2]), "+f"(d[b+3]), "+f"(d[b+4]), "+f"(d[b+5]), "+f"(d[b+6]), "+f"(d[b+7])
__device__ __forceinline__ void wgmma_n256(float (&d)[128], uint64_t da, uint64_t db, int scale_d) {
    asm volatile("{\n.reg .pred p;\nsetp.ne.b32 p, %130, 0;\n"
        "wgmma.mma_async.sync.aligned.m64n256k16.f32.bf16.bf16 {"
        "%0,%1,%2,%3,%4,%5,%6,%7,%8,%9,%10,%11,%12,%13,%14,%15,%16,%17,%18,%19,%20,%21,%22,%23,%24,%25,%26,%27,%28,%29,%30,%31,"
        "%32,%33,%34,%35,%36,%37,%38,%39,%40,%41,%42,%43,%44,%45,%46,%47,%48,%49,%50,%51,%52,%53,%54,%55,%56,%57,%58,%59,%60,%61,%62,%63,"
        "%64,%65,%66,%67,%68,%69,%70,%71,%72,%73,%74,%75,%76,%77,%78,%79,%80,%81,%82,%83,%84,%85,%86,%87,%88,%89,%90,%91,%92,%93,%94,%95,"
        "%96,%97,%98,%99,%100,%101,%102,%103,%104,%105,%106,%107,%108,%109,%110,%111,%112,%113,%114,%115,%116,%117,%118,%119,%120,%121,%122,%123,%124,%125,%126,%127"
        "}, %128, %129, p, 1, 1, 0, 1;\n}\n"
        : ACC8(d, 0), ACC8(d, 8), ACC8(d, 16), ACC8(d, 24), ACC8(d, 32), ACC8(d, 40), ACC8(d, 48), ACC8(d, 56),
          ACC8(d, 64), ACC8(d, 72), ACC8(d, 80), ACC8(d, 88), ACC8(d, 96), ACC8(d, 104), ACC8(d, 112), ACC8(d, 120)
        : "l"(da), "l"(db), "r"(scale_d));
}
template <int scale_d>
__device__ __forceinline__ void wgmma_n64_rs(float (&d)[32], uint32_t a0, uint32_t a1, uint32_t a2, uint32_t a3, uint32_t db) {
    asm volatile("{\n.reg .pred p;\n.reg .b64 db;\nsetp.ne.b32 p, %37, 0;\nmov.b64 db, {%36, 0x40000040};\n"
        "wgmma.mma_async.sync.aligned.m64n64k16.f32.bf16.bf16 {"
        "%0,%1,%2,%3,%4,%5,%6,%7,%8,%9,%10,%11,%12,%13,%14,%15,%16,%17,%18,%19,%20,%21,%22,%23,%24,%25,%26,%27,%28,%29,%30,%31"
        "}, {%32,%33,%34,%35}, db, p, 1, 1, 1;\n}\n"
        : ACC8(d, 0), ACC8(d, 8), ACC8(d, 16), ACC8(d, 24)
        : "r"(a0), "r"(a1), "r"(a2), "r"(a3), "r"(db), "n"(scale_d));
}
#define WG_FENCE() asm volatile("wgmma.fence.sync.aligned;" ::: "memory")
#define WG_COMMIT() asm volatile("wgmma.commit_group.sync.aligned;" ::: "memory")
#define WG_WAIT(n) asm volatile("wgmma.wait_group.sync.aligned " #n ";" ::: "memory")
template <int N> __device__ __forceinline__ void reg_fence(float (&d)[N]) {
    #pragma unroll
    for (int i = 0; i < N; i++) asm volatile("" : "+f"(d[i]) :: "memory");
}

__device__ __forceinline__ void wgmma_n256_rs(float (&d)[128], uint32_t a0, uint32_t a1, uint64_t db) {
    asm volatile("{\n.reg .pred p;\nsetp.ne.b32 p, 1, 0;\n"
        "wgmma.mma_async.sync.aligned.m64n256k16.f32.bf16.bf16 {"
        "%0,%1,%2,%3,%4,%5,%6,%7,%8,%9,%10,%11,%12,%13,%14,%15,%16,%17,%18,%19,%20,%21,%22,%23,%24,%25,%26,%27,%28,%29,%30,%31,"
        "%32,%33,%34,%35,%36,%37,%38,%39,%40,%41,%42,%43,%44,%45,%46,%47,%48,%49,%50,%51,%52,%53,%54,%55,%56,%57,%58,%59,%60,%61,%62,%63,"
        "%64,%65,%66,%67,%68,%69,%70,%71,%72,%73,%74,%75,%76,%77,%78,%79,%80,%81,%82,%83,%84,%85,%86,%87,%88,%89,%90,%91,%92,%93,%94,%95,"
        "%96,%97,%98,%99,%100,%101,%102,%103,%104,%105,%106,%107,%108,%109,%110,%111,%112,%113,%114,%115,%116,%117,%118,%119,%120,%121,%122,%123,%124,%125,%126,%127"
        "}, {%128, %129, %130, %130}, %131, p, 1, 1, 0;\n}\n"
        : ACC8(d, 0), ACC8(d, 8), ACC8(d, 16), ACC8(d, 24), ACC8(d, 32), ACC8(d, 40), ACC8(d, 48), ACC8(d, 56),
          ACC8(d, 64), ACC8(d, 72), ACC8(d, 80), ACC8(d, 88), ACC8(d, 96), ACC8(d, 104), ACC8(d, 112), ACC8(d, 120)
        : "r"(a0), "r"(a1), "r"(0u), "l"(db));
}
__device__ __forceinline__ void tma_fill(const CUtensorMap* maps, uint32_t dst, uint32_t bar, uint32_t moff, uint32_t c0, uint32_t c1, uint32_t c2) {
    mbar_expect_tx(bar, SLOT);
    asm volatile("cp.async.bulk.tensor.3d.shared::cluster.global.mbarrier::complete_tx::bytes [%0], [%1, {%3, %4, %5}], [%2];"
        :: "r"(dst), "l"(reinterpret_cast<const char*>(maps) + moff), "r"(bar), "r"(c0), "r"(c1), "r"(c2) : "memory");
}
__device__ __forceinline__ void ldg_v2(const void* p, uint32_t& x, uint32_t& y) { asm volatile("ld.global.nc.v2.u32 {%0,%1}, [%2];" : "=r"(x), "=r"(y) : "l"(p)); }
__device__ __forceinline__ bool elect_one() {
    uint32_t r; asm volatile("{\n.reg .pred p;\nelect.sync _|p, 0xffffffff;\nselp.u32 %0, 1, 0, p;\n}" : "=r"(r)); return r;
}
__device__ __forceinline__ void sts16(uint32_t a, uint32_t x) { asm volatile("st.shared.u16 [%0], %1;" :: "r"(a), "h"((uint16_t)x) : "memory"); }
__device__ __forceinline__ float rcp_fast(float v) { float r; asm("rcp.approx.ftz.f32 %0, %1;" : "=f"(r) : "f"(v)); return r; }
__device__ __forceinline__ float sqrt_fast(float v) { float r; asm("sqrt.approx.ftz.f32 %0, %1;" : "=f"(r) : "f"(v)); return r; }

struct Cx { float r, i; };
__device__ __forceinline__ Cx cmul(Cx a, Cx b) { return {fmaf(a.r, b.r, -a.i * b.i), fmaf(a.r, b.i, a.i * b.r)}; }
__device__ __forceinline__ Cx csqr(Cx a) { return {fmaf(a.r, a.r, -a.i * a.i), 2.f * (a.r * a.i)}; }
__device__ __forceinline__ Cx anchor(float lm, float th, float tl, float p) {
    float mag = ex2_fast(lm * p);
    float u = th * p;
    float f = fmaf(tl, p, u - rintf(u)) * 6.283185307179586f;
    return {mag * __cosf(f), mag * __sinf(f)};
}
__device__ __forceinline__ void hcmul(uint32_t pr, uint32_t pi, uint32_t y, uint32_t& orr, uint32_t& oi) {
    __half2 yr = __low2half2(H2(y)), yi = __high2half2(H2(y));
    orr = U32(__hfma2(H2(pr), yr, __hneg2(__hmul2(H2(pi), yi))));
    oi = U32(__hfma2(H2(pr), yi, __hmul2(H2(pi), yr)));
}

struct Maps { CUtensorMap m[3]; };

struct KPar {
    uint2 lar, aim, cre, cim, cre2, cim2; uint32_t ldt, dskr;
    __device__ __forceinline__ void load(const Params& P, int ch, int off) {
        const int po = ch * NMODE + off;
        ldg_v2(P.lar + po, lar.x, lar.y); ldg_v2(P.aim + po, aim.x, aim.y);
        ldg_v2(P.cre + po, cre.x, cre.y); ldg_v2(P.cim + po, cim.x, cim.y);
        asm volatile("ld.global.nc.u16 %0, [%1];" : "=r"(ldt) : "l"(P.ldt + ch));
        ldg_v2(P.cre + (po ^ 4), cre2.x, cre2.y); ldg_v2(P.cim + (po ^ 4), cim2.x, cim2.y);
        asm volatile("ld.global.nc.u16 %0, [%1];" : "=r"(dskr) : "l"(P.dsk + ch));
    }
};
struct KGen : KPar {
    float dt, cscale, yscale, dtap, acc[5][4], k2048;
    uint32_t zero;
    __device__ __forceinline__ void consts() {
        const float l = __uint_as_float(ldt << 16), t = l * 1.4426950408889634f;
        dt = rbf(ex2_fast(t) * fmaf(fmaf(l, 1.4426950408889634f, -t) + l * 1.925963033500e-8f, 0.6931471805599453f, 1.f));
        uint32_t mx = __vimax3_u16x2(__vimax3_u16x2(cre.x & 0x7fff7fffu, cre.y & 0x7fff7fffu, cim.x & 0x7fff7fffu),
                                     __vimax3_u16x2(cim.y & 0x7fff7fffu, cre2.x & 0x7fff7fffu, cre2.y & 0x7fff7fffu),
                                     __vmaxu2(cim2.x & 0x7fff7fffu, cim2.y & 0x7fff7fffu));
        mx = __reduce_max_sync(0xffffffffu, max(mx & 0xffffu, mx >> 16));
        zero = mx >> 16;
        const int ec = (int)(__float_as_uint(__uint_as_float(mx << 16) * 2.f * dt) >> 23) + 1, ed = (int)((dskr & 0x7fffu) >> 7) - 13;
        const uint32_t eb = min(max(max(ec, ed), 2), 253);
        const float inv = __uint_as_float((254 - eb) << 23);
        yscale = __uint_as_float(eb << 23);
        cscale = 2.f * dt * inv;
        dtap = __uint_as_float(dskr << 16) * inv;
        k2048 = 0.f;
        #pragma unroll
        for (int t5 = 0; t5 < 5; t5++) { acc[t5][0] = acc[t5][1] = acc[t5][2] = acc[t5][3] = 0.f; }
    }
    __device__ __forceinline__ void pass(uint32_t stg, int lane) {
        const float lar = bf_lo(this->lar.x), aim = bf_lo(this->aim.x);
        const Cx X0 = {bf_lo(cre.x) * cscale, bf_lo(cim.x) * cscale};
        this->lar.x = __funnelshift_r(this->lar.x, this->lar.y, 16); this->lar.y >>= 16; this->aim.x = __funnelshift_r(this->aim.x, this->aim.y, 16); this->aim.y >>= 16;
        cre.x = __funnelshift_r(cre.x, cre.y, 16); cre.y >>= 16; cim.x = __funnelshift_r(cim.x, cim.y, 16); cim.y >>= 16;
        const float lm = -rbf(ex2_fast(lar * 1.4426950408889634f)) * dt * 1.4426950408889634f;
        const float zi = aim * dt;
        const float th = zi * 0.15915494309189535f;
        const float tl = fmaf(zi, 0.15915494309189535f, -th) + zi * 6.4206382e-09f;
        const Cx E1 = anchor(lm, th, tl, 1.f), Y1 = anchor(lm, th, tl, 32.f);
        const Cx E2 = csqr(E1), E4 = csqr(E2), E8 = csqr(E4), E16 = csqr(E8), X1 = cmul(X0, E8);
        const Cx Y2 = csqr(Y1), G1 = csqr(Y2), G2 = csqr(G1), G4 = csqr(G2), G5 = cmul(G4, G1), G8 = csqr(G4);
        { const Cx Z = csqr(G8); k2048 += fmaf(X0.r, Z.r, -X0.i * Z.i); }
        const uint32_t sa = stg + lane * 16;
        __syncwarp();
        uint32_t a, bq, c, d, e, f, gq, hq;
        {
            const uint32_t xr01 = pack_f16(X0.r, X1.r), xn01 = pack_f16(-X0.i, -X1.i);
            const uint32_t y1 = pack_f16(Y1.r, -Y1.i), y2 = pack_f16(Y2.r, -Y2.i);
            uint32_t xr23, xn23;
            hcmul(xr01, xn01, pack_f16(E16.r, -E16.i), xr23, xn23);
            hcmul(xr01, xn01, y1, a, bq); hcmul(xr23, xn23, y1, c, d);
            sts128(sa + 0 * 512, xr01, xr23, a, c); sts128(sa + 2 * 512, xn01, xn23, bq, d);
            hcmul(a, bq, y2, e, f); hcmul(c, d, y2, gq, hq); hcmul(xr01, xn01, y2, a, bq); hcmul(xr23, xn23, y2, c, d);
            sts128(sa + 1 * 512, a, c, e, gq); sts128(sa + 3 * 512, bq, d, f, hq);
        }
        {
            const uint32_t r02 = pack_f16(1.f, E2.r), i02 = pack_f16(0.f, E2.i), e1 = pack_f16(E1.r, E1.i), e4 = pack_f16(E4.r, E4.i);
            const uint32_t g1 = pack_f16(G1.r, G1.i), g2 = pack_f16(G2.r, G2.i), g8 = pack_f16(G8.r, G8.i);
            uint32_t r46, i46, r13, i13, r57, i57;
            hcmul(r02, i02, e4, r46, i46); hcmul(r02, i02, e1, r13, i13); hcmul(r46, i46, e1, r57, i57);
            sts128(sa + 4 * 512, r02, r46, r13, r57); sts128(sa + 5 * 512, i02, i46, i13, i57);
            hcmul(r02, i02, g1, a, bq); hcmul(r46, i46, g1, c, d); hcmul(r13, i13, g1, e, f); hcmul(r57, i57, g1, gq, hq);
            sts128(sa + 6 * 512, a, c, e, gq); sts128(sa + 7 * 512, bq, d, f, hq);
            hcmul(a, bq, g2, e, f); hcmul(c, d, g2, gq, hq); hcmul(r02, i02, g2, a, bq); hcmul(r46, i46, g2, c, d);
            sts128(sa + 8 * 512, a, c, e, gq); sts128(sa + 9 * 512, bq, d, f, hq);
            const uint32_t r45 = pack_f16(G4.r, G5.r), i45 = pack_f16(G4.i, G5.i), g4 = __byte_perm(r45, i45, 0x5410);
            uint32_t r67, i67;
            hcmul(r45, i45, g2, r67, i67);
            hcmul(r45, i45, e4, a, bq); hcmul(r67, i67, e4, c, d);
            sts128(sa + 10 * 512, r45, r67, a, c); sts128(sa + 11 * 512, i45, i67, bq, d);
            hcmul(r45, i45, g4, a, bq); hcmul(r67, i67, g4, c, d); hcmul(r45, i45, g8, e, f); hcmul(r67, i67, g8, gq, hq);
            sts128(sa + 12 * 512, a, c, e, gq); sts128(sa + 13 * 512, bq, d, f, hq);
        }
        __syncwarp();
    }
    __device__ __forceinline__ void contract(uint32_t stg, int lane) {
        float (&kacc)[5][4] = acc;
        #pragma unroll
        for (int ks = 0; ks < 4; ks++) {
            const uint32_t la = stg + (lane >> 3) * 512 + (ks * 8 + (lane & 7)) * 16;
            uint32_t a0, a1, a2, a3, b0, b1, b2, b3, c0, c1, c2, c3, d0, d1;
            ldsm4t(la, a0, a1, a2, a3);
            ldsm4t(la + 4 * 512, b0, b1, b2, b3);
            ldsm4t(la + 8 * 512, c0, c1, c2, c3);
            ldsm2t(la + 12 * 512, d0, d1);
            mma_f16(kacc[0], a0, a1, a2, a3, b0, b1); mma_f16(kacc[1], a0, a1, a2, a3, b2, b3);
            mma_f16(kacc[2], a0, a1, a2, a3, c0, c1); mma_f16(kacc[3], a0, a1, a2, a3, c2, c3);
            mma_f16(kacc[4], a0, a1, a2, a3, d0, d1);
        }
    }
    __device__ __forceinline__ void deposit(uint32_t dep, int lane, bool lead) {
        if (lead) acc[0][0] += dtap;
        const float k512 = __shfl_sync(0xffffffffu, acc[3][0], 0);
        if (lane == 31) acc[2][3] -= k512;
        k2048 = (float)__reduce_add_sync(0xffffffffu, __float2int_rn(k2048 * 4194304.f)) * (1.f / 4194304.f);
        #pragma unroll
        for (int t = 0; t < 5; t++) {
            sts32(dep + t * 256 + lane * 4, pack_f16(acc[t][0], acc[t][1]));
            sts32(dep + t * 256 + 128 + lane * 4, pack_f16(acc[t][2], acc[t][3]));
        }
        sts128(dep + 1280, __float_as_uint(k2048), __float_as_uint(yscale), 0, 0);
    }
};

struct Taps { uint32_t kv[5]; float k2, yscale; };
template <int ND>
__device__ __forceinline__ Taps sum_deposits(uint32_t d0, uint32_t s1, uint32_t s2, int tt) {
    Taps T; float ks[10]; T.k2 = 0.f;
    #pragma unroll
    for (int t = 0; t < 10; t++) ks[t] = 0.f;
    #pragma unroll
    for (int i = 0; i < ND; i++) {
        const uint32_t og = d0 + (i & 1) * s1 + (i >> 1) * s2;
        #pragma unroll
        for (int t = 0; t < 5; t++) { const float2 v = __half22float2(H2(lds32(og + t * 256 + tt * 4))); ks[2 * t] += v.x; ks[2 * t + 1] += v.y; }
        T.k2 += ldsf(og + 1280);
    }
    T.yscale = ldsf(d0 + 1284);
    #pragma unroll
    for (int t = 0; t < 5; t++) T.kv[t] = pack_f16(ks[2 * t], ks[2 * t + 1]);
    return T;
}
__device__ __forceinline__ void scatter_taps(Taps& T, uint32_t tb, int tt) {
    const int lane = tt & 31, w = tt >> 5, g = lane >> 2, q = lane & 3;
    uint32_t (&kv)[5] = T.kv;
    const int jj = g + 8 * w;
    const uint32_t tab = tb + T_TAB;
    const uint32_t d01 = tab + TD0 + 2 * (544 - (8 * jj + (q & 1) * 4 + (q >> 1)));
    #pragma unroll
    for (int t = 0; t < 2; t++) {
        sts16(d01 - t * 256, kv[t]); sts16(d01 - t * 256 + (TD1 + 2), kv[t]);
        sts16(d01 - t * 256 - 4, kv[t] >> 16); sts16(d01 - t * 256 - 4 + (TD1 + 2), kv[t] >> 16);
    }
    const int p2 = 256 + 128 * (q >> 1) + 4 * (q & 1) + 8 * jj;
    const uint32_t d2 = tab + TD0 + 2 * (544 - p2);
    sts32(d2 - 4, __byte_perm(kv[2], 0, 0x1032));
    sts32(d2 + TD1, __byte_perm(kv[2], 0, 0x1010));
    sts16(d2, kv[2]); sts16(d2 + TD1 - 2, kv[2] >> 16);
    if (p2 != 256) { sts16(d2 + 2, kv[2]); sts16(d2 + TD1 + 4, kv[2]); }
    const uint32_t d3 = tab + TT2 + (q < 2 ? TT2SZ + 2 : 0) + 2 * (142 - 64 - 32 * (q & 1) - jj);
    sts16(d3, kv[3]); sts16(d3 - 32, kv[3] >> 16);
    uint32_t d4 = tab + TT3 + ((jj & 1) ? 0 : TT3SZ + 2) + 2 * (136 - 64 - 16 * q - (jj >> 1));
    sts16(d4 - 16, kv[4] >> 16); sts16(d4 - 16 + 194, kv[4] >> 16);
    if (tt == 0) {
        sts16(tab + TT2 + TT2SZ + 2 * (142 - 127), kv[4]);
        kv[4] = pack_f16(T.k2, 0.f); d4 = tab + TT3 + TT3SZ + 2 * (136 - 127);
    }
    sts16(d4, kv[4]); sts16(d4 + 194, kv[4]);
}

struct LnRows {
    uint32_t xb[14], piv;
    __device__ __forceinline__ void load(const Params& P, int b, int at) {
        const __nv_bfloat16* xp = P.x + (b * 16 + (at >> 4)) * DM;
        #pragma unroll
        for (int k = 0; k < 7; k++) ldg_v2(xp + k * 64 + (at & 15) * 4, xb[2 * k], xb[2 * k + 1]);
        asm volatile("ld.global.nc.u16 %0, [%1];" : "=r"(piv) : "l"(xp));
    }
    __device__ __forceinline__ void run(const Params& P, int b, int at, uint32_t lb, uint32_t tag) {
        asm volatile("" : "+r"(piv));
        const float pv = __uint_as_float(piv << 16);
        float s1 = 0.f, s2 = 0.f, s3 = 0.f, s4 = 0.f;
        #pragma unroll
        for (int k = 0; k < 14; k++) {
            asm volatile("" : "+r"(xb[k]));
            const float a = bf_lo(xb[k]) - pv, c = bf_hi(xb[k]) - pv;
            s1 += a; s3 += c; s2 = fmaf(a, a, s2); s4 = fmaf(c, c, s4);
        }
        s1 += s3; s2 += s4;
        #pragma unroll
        for (int o = 8; o > 0; o >>= 1) { s1 += __shfl_xor_sync(0xffffffffu, s1, o); s2 += __shfl_xor_sync(0xffffffffu, s2, o); }
        const float dm = s1 * (1.f / DM), mean = dm + pv;
        const float var = fmaxf(fmaf(-dm, dm, s2 * (1.f / DM)), 0.f);
        const float den = rbf(sqrt_fast(rbf(rbf(var) + 1e-5f))), inv = rcp_fast(den);
        const uint32_t m2 = pack_bf16(mean, mean);
        #pragma unroll
        for (int k = 0; k < 7; k++) {
            const uint32_t d0 = U32(__hsub2(B2(xb[2 * k]), B2(m2))), d1 = U32(__hsub2(B2(xb[2 * k + 1]), B2(m2)));
            asm volatile("st.shared.v2.u32 [%0], {%1,%2};" :: "r"(lb + (at >> 4) * 912 + k * 128 + (at & 15) * 8),
                         "r"(pack_f16(bf_lo(d0) * inv, bf_hi(d0) * inv)), "r"(pack_f16(bf_lo(d1) * inv, bf_hi(d1) * inv)) : "memory");
        }
        const float mb = bf_hi(m2);
        const float den2 = rbf(sqrt_fast(rbf(rbf(var * inv * inv) + 1e-5f)));
        const float ia = den * den2, r = -fmaf(rbf((mean - mb) * inv), den, mb);
        const float rh = rbf(r), ih = rbf(ia);
        if ((at & 15) == 0)
            st_relaxed_v4(P.S->stats + b * 16 + (at >> 4),
                          make_uint4(pack_bf16(rh, r - rh), pack_bf16(rh, ih), pack_bf16(ia - ih, 0.f), (__float_as_uint(rcp_fast(ia)) & ~1u) | tag));
    }
};
__device__ __forceinline__ void ln_publish(const Params& P, int b, int at, uint32_t lb, uint32_t tag) {
    const int lane = at & 31, mi = lane >> 3, ri = lane & 7;
    const uint32_t la = lb + ((ri >> 1) * 4 + (ri & 1) + (mi & 1) * 2) * 912 + (mi >> 1) * 16 + (at >> 5) * 224;
    __half* dp = P.S->xnT + ((at >> 5) * 112 + (lane >> 2)) * LSEQ + b * 16 + ((lane & 3) ^ ((b >> 1) & 2)) * 4;
    #pragma unroll
    for (int i = 0; i < 7; i++) {
        uint32_t r0, r1, r2, r3;
        ldsm4t(la + i * 32, r0, r1, r2, r3);
        st_relaxed_v2(dp + i * 16 * LSEQ, (r0 & ~1u) | tag, r1);
        st_relaxed_v2(dp + (i * 16 + 8) * LSEQ, (r2 & ~1u) | tag, r3);
    }
    if (lane == 0) red_relaxed(P.S->hint + (8 + (at >> 5)) * 32);
}

__device__ __forceinline__ void fetch_x(const Params& P, int ch, uint32_t tb, int tt) {
    #pragma unroll
    for (int i = 0; i < 4; i++)
        asm volatile("cp.async.cg.shared.global [%0], [%1], 16;" :: "r"(tb + T_XP + 512 + tt * 16 + i * 1024), "l"(P.S->xnT + ch * LSEQ + (i * 64 + tt) * 8) : "memory");
}
__device__ __forceinline__ uint32_t swz(int u) { return (uint32_t)(u ^ ((u >> 3) & 1)) * 16; }
template <int NU, bool ALL>
__device__ __forceinline__ void box_units(uint32_t tb, int u) {
    uint32_t e[12 + 4 * NU], o[10 + 4 * NU], qq[10 + 4 * NU];
    #pragma unroll
    for (int i = ALL ? 0 : 1; i < 3 + NU; i++) {
        const uint4 v = lds128(tb + T_XP + swz(u + 29 + i));
        e[4 * i] = v.x; e[4 * i + 1] = v.y; e[4 * i + 2] = v.z; e[4 * i + 3] = v.w;
    }
    #pragma unroll
    for (int k = ALL ? 2 : 7; k < 10 + 4 * NU; k++) { o[k] = __byte_perm(e[k], e[k + 1], 0x5432); qq[k] = hadd2u(e[k], o[k]); }
    #pragma unroll
    for (int n = 0; n < NU; n++) {
        uint32_t r2o[4], r2e[4], r3o[4], r3e[4];
        #pragma unroll
        for (int pp = 0; pp < 4; pp++) {
            const int p = 4 * n + pp;
            const uint32_t d8 = hadd2u(qq[8 + p], qq[7 + p]);
            r2o[pp] = hadd2u(qq[10 + p], o[9 + p]);
            r2e[pp] = hadd2u(e[9 + p], d8);
            if (ALL) {
                r3o[pp] = hadd2u(hadd2u(qq[9 + p], o[6 + p]), d8);
                r3e[pp] = hadd2u(hadd2u(e[6 + p], hadd2u(qq[5 + p], qq[4 + p])), hadd2u(qq[3 + p], qq[2 + p]));
            }
        }
        sts128(tb + T_U2O + (16 + u + n) * 16, r2o[0], r2o[1], r2o[2], r2o[3]);
        sts128(tb + T_U2O + U2SZ + (16 + u + n) * 16, r2e[0], r2e[1], r2e[2], r2e[3]);
        if (ALL) {
            const uint32_t a = tb + T_U3O + swz(u + n);
            sts128(a, r3o[0], r3o[1], r3o[2], r3o[3]);
            sts128(a + U3SZ, r3e[0], r3e[1], r3e[2], r3e[3]);
            sts128(a + 2 * U3SZ, qq[10 + 4 * n], qq[11 + 4 * n], qq[12 + 4 * n], qq[13 + 4 * n]);
        }
    }
}
__device__ __forceinline__ void prep(const Params& P, int ch, uint32_t tb, int tt, int bar, uint32_t tag) {
    sts128(tb + (tt < 32 ? T_XP + tt * 16 : T_U2O + ((tt >> 4) & 1) * U2SZ + (tt & 15) * 16), 0, 0, 0, 0);
    #pragma unroll 1
    for (int it = 0; it < (1 << 16); it++) {
        asm volatile("cp.async.wait_all;" ::: "memory");
        __syncwarp();
        uint32_t m = 0;
        #pragma unroll
        for (int i = 0; i < 2; i++) {
            uint32_t r0, r1, r2, r3, r4, r5, r6, r7;
            ldsm4(tb + T_XP + 512 + tt * 16 + i * 2048, r0, r1, r2, r3);
            ldsm4(tb + T_XP + 1536 + tt * 16 + i * 2048, r4, r5, r6, r7);
            m |= (r0 ^ tag) | (r1 ^ tag) | (r2 ^ tag) | (r3 ^ tag) | (r4 ^ tag) | (r5 ^ tag) | (r6 ^ tag) | (r7 ^ tag);
        }
        if (!__any_sync(0xffffffffu, m & ~tt & 1u)) break;
        __nanosleep(100);
        fetch_x(P, ch, tb, tt);
    }
    bar_sync(bar, 64);
    #pragma unroll 1
    for (int u = 128 + (tt ^ 32); u <= 192; u += 64) box_units<1, false>(tb, u);
    box_units<2, true>(tb, 2 * tt);
    bar_sync(bar, 64);
}
__device__ __forceinline__ void convolve(const Params& P, int ch, uint32_t tb, int tt, int bar, int cw, int ca) {
    const int lane = tt & 31, w = tt >> 5, g = lane >> 2, q = lane & 3;
    const uint32_t stg = tb + T_STG + w * STG_W;
    float acc[16][4];
    #pragma unroll
    for (int a = 0; a < 16; a++) { acc[a][0] = acc[a][1] = acc[a][2] = acc[a][3] = 0.f; }
    const int dl = g - 2 * q;
    int xu = 2 * (16 + 8 * (lane >> 4) + (lane & 7) - w) + ((lane >> 3) & 1);
    const uint32_t xa0 = tb + T_XP + swz(xu);
    uint32_t A[4][4];
    const uint32_t ra0 = tb + T_TAB + ((g & 1) ? TD1 + 2 : TD0) + 2 * (544 - dl) - 32 * w;
    {
        uint32_t xa = xa0, ra = ra0;
        float accm[8][4];
        #pragma unroll
        for (int a = 0; a < 8; a++) { accm[a][0] = accm[a][1] = accm[a][2] = accm[a][3] = 0.f; }
        uint32_t F[2][4];
        #pragma unroll
        for (int i = 0; i < 4; i++) { A[i][0] = lds32(ra - i * 256); A[i][1] = lds32(ra - i * 256 - 16); A[i][2] = lds32(ra - i * 256 + 16); A[i][3] = lds32(ra - i * 256); }
        ldsm4(xa, F[0][0], F[0][1], F[0][2], F[0][3]);
        if (cw >= 0) bar_sync(cw, 128);
        #pragma unroll 1
        for (int it = 0; it < 4; it++) {
            if (it == 3 && ca >= 0) bar_arrive(ca, 128);
            ra -= 64; xu -= 4;
            const uint32_t xn = tb + T_XP + swz(xu);
            uint32_t S[2][4];
            #pragma unroll
            for (int k = 0; k < 4; k++) { S[0][k] = hadd2u(A[0][k], A[1][k]); S[1][k] = hadd2u(A[2][k], A[3][k]); }
            #pragma unroll
            for (int m = 0; m < 8; m++) {
                const int c = m & 1;
                ldsm4(m < 7 ? xa + (m + 1) * 512 : xn, F[c ^ 1][0], F[c ^ 1][1], F[c ^ 1][2], F[c ^ 1][3]);
                const uint32_t s0 = hadd2u(F[c][0], F[c][2]), s1 = hadd2u(F[c][1], F[c][3]);
                if (m < 7) {
                    mma_f16(acc[2 * m + 2], A[2][0], A[2][1], A[2][2], A[2][3], F[c][0], F[c][1]);
                    mma_f16(accm[m + 1], A[3][0], A[3][1], A[3][2], A[3][3], F[c][2], F[c][3]);
                    mma_f16(acc[2 * m + 3], S[1][0], S[1][1], S[1][2], S[1][3], s0, s1);
                } else {
                    #pragma unroll
                    for (int i = 2; i < 4; i++) { A[i][0] = lds32(ra - i * 256); A[i][1] = lds32(ra - i * 256 - 16); A[i][2] = lds32(ra - i * 256 + 16); A[i][3] = lds32(ra - i * 256); }
                }
                mma_f16(acc[2 * m], A[0][0], A[0][1], A[0][2], A[0][3], F[c][0], F[c][1]);
                mma_f16(accm[m], A[1][0], A[1][1], A[1][2], A[1][3], F[c][2], F[c][3]);
                mma_f16(acc[2 * m + 1], S[0][0], S[0][1], S[0][2], S[0][3], s0, s1);
            }
            #pragma unroll
            for (int i = 0; i < 2; i++) { A[i][0] = lds32(ra - i * 256); A[i][1] = lds32(ra - i * 256 - 16); A[i][2] = lds32(ra - i * 256 + 16); A[i][3] = lds32(ra - i * 256); }
            xa = xn;
        }
        #pragma unroll
        for (int m = 0; m < 8; m++) {
            #pragma unroll
            for (int e = 0; e < 4; e++) {
                acc[2 * m + 1][e] -= acc[2 * m][e] + accm[m][e];
                if (m > 0) acc[2 * m][e] += accm[m - 1][e];
            }
        }
    }
    const uint32_t lo = ((lane >> 4) * 8 + (lane & 7)) * 32 + (((lane >> 3) ^ (lane >> 2)) & 1) * 16, va = tb + T_U3O + lo;
    {
        uint32_t tp[10], t3[8][2];
        const uint32_t ta = tb + T_TAB + TT2 + w * TT2SZ + 2 * (142 - 56 - 2 * (g - q));
        #pragma unroll
        for (int i = 0; i < 10; i++) tp[i] = lds32(ta - i * 16);
        const uint32_t t3a = tb + T_TAB + TT3 + w * TT3SZ + ((g & 1) ? 194 : 0) + 2 * (136 - 56 - dl);
        #pragma unroll
        for (int i = 0; i < 8; i++) { t3[i][0] = lds32(t3a - i * 16 - 16); t3[i][1] = lds32(t3a - i * 16); }
        const uint32_t ua = tb + T_U2O + w * U2SZ + (16 + (lane >> 4) * 8 + ((lane >> 3) & 1) + (lane & 7)) * 16;
        #pragma unroll
        for (int kk = -1; kk <= 5; kk++) {
            uint32_t a0, a1, a2, a3, c0, c1, c2, c3;
            ldsm4t(ua + kk * 256, a0, a1, a2, a3);
            if (kk < 5) ldsm4t(ua + (kk + 7) * 256, c0, c1, c2, c3);
            #pragma unroll
            for (int e = 4; e <= 8; e++) {
                mma_f16(acc[kk + e], a0, a1, a2, a3, tp[2 * (e - 4) + 1], tp[2 * (e - 4)]);
                if (kk < 5 && kk + 7 + e < 16) mma_f16(acc[kk + 7 + e], c0, c1, c2, c3, tp[2 * (e - 4) + 1], tp[2 * (e - 4)]);
            }
        }
        #pragma unroll
        for (int kk = 0; kk < 4; kk++) {
            uint32_t a0, a1, a2, a3;
            ldsm4t(va + w * U3SZ + kk * 512, a0, a1, a2, a3);
            #pragma unroll
            for (int a = 15; a >= 8 + 2 * kk; a--) mma_f16(acc[a], a0, a1, a2, a3, t3[a - 2 * kk - 8][0], t3[a - 2 * kk - 8][1]);
        }
    }
    if (w) {
        uint32_t kx = lds32(tb + T_TAB + TT2 + TT2SZ + 2 * (142 - 128));
        kx = dl == 0 ? kx >> 16 : (dl == 1 ? kx : 0u);
        #pragma unroll
        for (int kk = 0; kk < 4; kk++) {
            uint32_t a0, a1, a2, a3;
            ldsm4t(va + 2 * U3SZ + kk * 512, a0, a1, a2, a3);
            mma_f16(acc[8 + 2 * kk], a0, a1, a2, a3, kx, 0u);
            mma_f16(acc[9 + 2 * kk], a0, a1, a2, a3, 0u, kx);
        }
    } else {
        const uint32_t a0 = A[3][0], a1 = A[3][1], a2 = A[3][2], a3 = A[3][3];
        #pragma unroll
        for (int m = 0; m < 12; m += 2) {
            uint32_t f0, f1, f2, f3;
            ldsm4(xa0 + m * 256, f0, f1, f2, f3);
            mma_f16(acc[m + 4], a0, a1, a2, a3, f0, f1);
            mma_f16(acc[m + 5], a0, a1, a2, a3, f2, f3);
        }
    }
    const uint32_t done_bar = tb + (O_BAR + 14 * 8 - O_AUX) - (bar - 1) * TEAM;
    if (w) {
        #pragma unroll
        for (int a = 0; a < 8; a++) {
            sts128(stg + a * 512 + lane * 16, __float_as_uint(acc[a][0]), __float_as_uint(acc[a][1]), __float_as_uint(acc[a][2]), __float_as_uint(acc[a][3]));
            acc[a][0] = acc[8 + a][0]; acc[a][1] = acc[8 + a][1]; acc[a][2] = acc[8 + a][2]; acc[a][3] = acc[8 + a][3];
        }
    } else {
        #pragma unroll
        for (int a = 8; a < 16; a++)
            sts128(stg + (a - 8) * 512 + lane * 16, __float_as_uint(acc[a][0]), __float_as_uint(acc[a][1]), __float_as_uint(acc[a][2]), __float_as_uint(acc[a][3]));
    }
    bar_sync(bar, 64);
    const __nv_bfloat162 ys2 = B2(__byte_perm(lds32(tb + T_TAB + TABSZ), 0, 0x3232));
    const uint32_t tag = lds32(tb + T_TAB + TABSZ + 4) & 1;
    uint4 o[8];
    #pragma unroll
    for (int a = 0; a < 8; a++) o[a] = lds128(tb + T_STG + (w ^ 1) * STG_W + lane * 16 + a * 512);
    #pragma unroll
    for (int a = 0; a < 8; a++) {
        o[a].x = U32(__hmul2(B2(pack_bf16(__uint_as_float(o[a].x) + acc[a][0], __uint_as_float(o[a].y) + acc[a][1])), ys2));
        o[a].y = U32(__hmul2(B2(pack_bf16(__uint_as_float(o[a].z) + acc[a][2], __uint_as_float(o[a].w) + acc[a][3])), ys2));
    }
    #pragma unroll
    for (int i = 0; i < 4; i++) stsm4t(stg + 4096 + i * 512 + lo, o[2 * i].x, o[2 * i].y, o[2 * i + 1].x, o[2 * i + 1].y);
    __syncwarp();
    if (ch < 2 * NMLP && lane == 0) mbar_arrive(done_bar);
    __nv_bfloat16* sp = P.S->sT + ch * LSEQ + w * 1024 + lane * 8;
    #pragma unroll
    for (int i = 0; i < 4; i++) { uint4 v = lds128(stg + 4096 + i * 512 + swz(lane)); v.x = (v.x & ~1u) | tag; st_relaxed_v4(sp + i * 256, v); }
    if (lane == 0) red_relaxed(P.S->hint + (1 + (ch >> 6)) * 32);
}

__global__ void __launch_bounds__(384, 1)
fused_kernel(const Params P, const __grid_constant__ Maps maps) {
    extern __shared__ unsigned char smem_raw[];
    const int tid = threadIdx.x;
    const int warp = tid >> 5, lane = tid & 31, b = blockIdx.x;
    const bool is_mlp = b < NMLP;
    const int team = is_mlp ? (warp >> 1) & 1 : warp >> 1, tt = tid & 63;
    int ch = is_mlp ? 2 * b + team : 2 * NMLP + (b - NMLP) * 6 + team;
    KGen K; LnRows L;
    K.load(P, (is_mlp && warp < 8) ? min(CH_EXP + b, DM - 1) : ch, lane * 8 + ((is_mlp && warp < 8) ? warp & 4 : (warp & 1) * 4));
    const int uw = __shfl_sync(0xffffffffu, warp, 0);
    const bool consumer = is_mlp && uw < 8, do_ln = (is_mlp ? uw < 8 : uw >= 4) && b < 128;
    const int lt = is_mlp ? tid : tid - 128;
    uint32_t epoch = 0;
    if (lane == 0) epoch = ld_relaxed(P.S->cnt + b * 8);
    const uint32_t sb = (smem_u32(smem_raw) + 1023) & ~1023u;
    const int mt = b & 15, j = b >> 4;
    const uint32_t tb = sb + (is_mlp ? O_AUX : 0) + team * TEAM;
    uint32_t stg;
    if (consumer) {
        if (elect_one()) {
            mbar_init(sb + O_BAR + uw * 8, uw < 7 ? 3 : 2);
            mbar_init(sb + O_BAR + 64 + uw * 8, uw == 6 ? 4 : 2);
            asm volatile("fence.mbarrier_init.release.cluster;" ::: "memory");
            if (uw < 2) {
                tma_fill(maps.m, sb + uw * 3 * SLOT, sb + O_BAR + uw * 8, 0, uw * 64, mt * 128, 0);
                tma_fill(maps.m, sb + (uw * 3 + 1) * SLOT, sb + O_BAR + uw * 8, 128, 0, uw * 64, j * 4);
                tma_fill(maps.m, sb + (uw * 3 + 2) * SLOT, sb + O_BAR + uw * 8, 128, 0, uw * 64 + 32, j * 4);
            }
        }
        __syncwarp();
        if (uw == 7) {
            const int f = lane + FT0, kc = (f * 43) >> 7, r3 = f - kc * 3, n2 = (f - 21) >> 1;
            int cn = j + 1 + n2; if (cn >= 7) cn -= 7;
            uint32_t grp = kc, moff = 0, c0 = kc * 64, c1 = mt * 128, c2 = 0;
            if (f >= 21) { grp = 7 + n2; moff = 256; c0 = cn * 64; c1 = j * 256 + ((f - 21) & 1) * 128; }
            else if (r3 != 0) { moff = 128; c0 = 0; c1 = kc * 64 + (r3 - 1) * 32; c2 = j * 4; }
            sts128(sb + O_FILL + lane * 32, sb + (f - ((f * 57) >> 9) * NS) * SLOT, sb + O_BAR + grp * 8, moff, c0);
            sts128(sb + O_FILL + lane * 32 + 16, c1, c2, 0, 0);
            if (lane < 16) sts32(sb + O_REL + lane * 4, 0);
        }
        bar_sync(BAR_INIT, 256);
        stg = uw < 6 ? sb + 6 * SLOT + uw * STG_W : sb + O_AUX + TEAM + (uw - 6) * STG_W;
    } else {
        if (do_ln) L.load(P, b, lt);
        #pragma unroll 1
        for (int i = tt; i < TABSZ / 16; i += 64) sts128(tb + T_TAB + i * 16, 0, 0, 0, 0);
        stg = tb + T_STG + (uw & 1) * STG_W;
    }
    auto fetch_part = [&](int step, int bar) {
        int src = j - 1 - step; if (src < 0) src += 7;
        mbar_expect_tx(sb + O_BAR + bar * 8, 16384);
        asm volatile("cp.async.bulk.shared::cluster.global.mbarrier::complete_tx::bytes [%0], [%1], 16384, [%2];"
                     :: "r"(sb + step * SLOT), "l"(P.S->part + ((mt * 7 + j) * 7 + src) * 1024), "r"(sb + O_BAR + bar * 8) : "memory");
    };
    auto release = [&](int grp, int f0, int n) {
        unsigned old = 0;
        if (lane == 0) asm volatile("atom.relaxed.cta.shared.inc.u32 %0, [%1], 7;" : "=r"(old) : "r"(sb + O_REL + grp * 4) : "memory");
        old = __shfl_sync(0xffffffffu, old, 0);
        if (old == 7 && lane < n && f0 + lane < NFILL) {
            const uint4 e0 = lds128(sb + O_FILL + (f0 - FT0 + lane) * 32), e1 = lds128(sb + O_FILL + (f0 - FT0 + lane) * 32 + 16);
            tma_fill(maps.m, e0.x, e0.y, e0.z, e0.w, e1.x, e1.y);
        }
        __syncwarp();
        return old == 7;
    };
    K.consts();
    if (consumer) {
        if (tid < 112) asm volatile("prefetch.global.L2 [%0];" :: "l"(P.x + b * 16 * DM + tid * 64 + K.zero));
        if (uw == 2 && mt < 10 && elect_one())
            asm volatile("cp.async.bulk.prefetch.tensor.3d.L2.global [%0, {%1, %2, %3}];" :: "l"(&maps.m[1]), "r"(0), "r"(128 + mt * 32 + K.zero), "r"(j * 4) : "memory");
        __syncwarp();
    }
    if (consumer) {
        if (uw & 2) { K.lar.x = K.lar.y; K.aim.x = K.aim.y; K.cre.x = K.cre.y; K.cim.x = K.cim.y; }
        const int sh = (uw & 1) * 16;
        K.lar.x >>= sh; K.aim.x >>= sh; K.cre.x >>= sh; K.cim.x >>= sh;
    }
    epoch = __shfl_sync(0xffffffffu, epoch, 0) + 1;
    uint32_t tag = epoch & 1;
    #pragma unroll 1
    for (int ps = consumer ? 3 : 0; ; ps++) {
        const uint32_t lb = sb + (is_mlp ? O_AUX : 6 * TEAM);
        if (ps == 4) {
            K.deposit(consumer ? sb + O_DEP + uw * DEPSZ : stg, lane, (consumer ? tid : tt) == 0);
            if (consumer) { asm volatile("fence.proxy.async.shared::cta;" ::: "memory"); release(13, 6, 3); }
        }
        if (do_ln && ps == (is_mlp ? 4 : 0)) {
            L.run(P, b, lt, lb, tag);
            if (!is_mlp && uw < 8) bar_arrive(BAR_D, 256);
        }
        if (uw >= 8 && b < 128 && ps == (is_mlp ? 2 : 0)) {
            const int at = tid & 127;
            uint32_t wv[28];
            if (is_mlp) {
                const __nv_bfloat16* wp = P.w1 + ((b & 3) * 112 + (at >> 4)) * FF + (b >> 2) * 64 + (at & 15) * 4;
                #pragma unroll
                for (int r = 0; r < 14; r++) ldg_v2(wp + r * 8 * FF, wv[2 * r], wv[2 * r + 1]);
            }
            bar_sync(BAR_D, is_mlp ? 384 : 256);
            ln_publish(P, b, at, lb, tag);
            if (is_mlp) {
                float c[4] = {0.f, 0.f, 0.f, 0.f};
                #pragma unroll
                for (int r = 0; r < 28; r++) { c[(r & 1) * 2] += bf_lo(wv[r]); c[(r & 1) * 2 + 1] += bf_hi(wv[r]); }
                #pragma unroll
                for (int i = 0; i < 4; i++) c[i] += __shfl_xor_sync(0xffffffffu, c[i], 16);
                if (lane < 16) sts128(sb + O_CSS + (at >> 5) * 256 + lane * 16, __float_as_uint(c[0]), __float_as_uint(c[1]), __float_as_uint(c[2]), __float_as_uint(c[3]));
                bar_sync(BAR_AUX, 128);
                if (team == 0) {
                    const float t = (ldsf(sb + O_CSS + at * 4) + ldsf(sb + O_CSS + 256 + at * 4)) + (ldsf(sb + O_CSS + 512 + at * 4) + ldsf(sb + O_CSS + 768 + at * 4));
                    asm volatile("st.relaxed.gpu.global.u32 [%0], %1;" :: "l"(P.S->cs + ((b >> 2) * 64 + at) * 4 + (b & 3)), "r"((__float_as_uint(t) & ~1u) | tag) : "memory");
                    if (at == 0) P.S->cnt[b * 8] = epoch;
                } else if (CH_EXP + b < DM) {
                    const Taps E = sum_deposits<8>(sb + O_DEP, DEPSZ, 2 * DEPSZ, tt);
                    st_relaxed_v4(P.S->kexp + b * 128 + tt, make_uint4(E.kv[0], E.kv[1], E.kv[2], (__float_as_uint(E.k2) & ~1u) | tag));
                    st_relaxed_v4(P.S->kexp + b * 128 + 64 + tt, make_uint4(E.kv[3], E.kv[4], __float_as_uint(E.yscale), tag));
                }
            }
        }
        if (ps == 4) break;
        K.pass(stg, lane);
        if (consumer) L.load(P, b, lt);
        if (is_mlp && uw >= 8 && ps == 2) {
            const int at = tid & 127;
            bar_sync(BAR_AUX, 128);
            const uint32_t bb = __ldg(reinterpret_cast<const uint32_t*>(P.b1 + j * 256 + at * 2));
            const uint32_t b2w = __ldg(reinterpret_cast<const uint32_t*>(P.b2 + j * 64 + lane * 2));
            uint4 st, c0, c1;
            #pragma unroll 1
            for (int it = 0; it < (1 << 16); it++) {
                st = ld_relaxed_v4(P.S->stats + mt * 128 + at);
                c0 = ld_relaxed_4x32(P.S->cs + (j * 256 + at * 2) * 4); c1 = ld_relaxed_4x32(P.S->cs + (j * 256 + at * 2) * 4 + 4);
                if (!__any_sync(0xffffffffu, ((st.w ^ tag) | (c0.x ^ tag) | (c0.y ^ tag) | (c0.z ^ tag) | (c0.w ^ tag) | (c1.x ^ tag) | (c1.y ^ tag) | (c1.z ^ tag) | (c1.w ^ tag)) & 1u)) break;
                __nanosleep(100);
            }
            sts128(sb + O_STATS + at * 16, st.x, st.y, st.z, st.w);
            if (at < 32) asm volatile("st.shared.v2.f32 [%0], {%1,%2};" :: "r"(sb + O_B2 + at * 8), "f"(0.5f * bf_lo(b2w)), "f"(0.5f * bf_hi(b2w)) : "memory");
            const float cx = (__uint_as_float(c0.x) + __uint_as_float(c0.y)) + (__uint_as_float(c0.z) + __uint_as_float(c0.w));
            const float cy = (__uint_as_float(c1.x) + __uint_as_float(c1.y)) + (__uint_as_float(c1.z) + __uint_as_float(c1.w));
            const uint32_t ch2 = pack_bf16(cx, cy), cl2 = pack_bf16(cx - bf_lo(ch2), cy - bf_hi(ch2));
            sts128(sb + O_BEXT + at * 32, __byte_perm(ch2, 0, 0x1010), __byte_perm(cl2, bb, 0x5410), bb & 0xffffu, 0);
            sts128(sb + O_BEXT + at * 32 + 16, __byte_perm(ch2, 0, 0x3232), __byte_perm(cl2, bb, 0x7632), bb >> 16, 0);
            asm volatile("fence.proxy.async.shared::cta;" ::: "memory");
            bar_arrive(BAR_A, 256); bar_arrive(BAR_A2, 256);
        }
        K.contract(stg, lane);
    }

    if (consumer) {
        const int g = lane >> 2, q = lane & 3, wg = uw >> 2;
        bar_sync(BAR_D, 384);
        uint32_t h[64];
        {
            float acc[128];
            uint32_t st = sb;
            #pragma unroll 1
            for (int s = 0; s < 7; s++) {
                if (s == 5 && wg == 1) { WG_WAIT(0); release(4, 21, 3); bar_sync(BAR_PP, 256); }
                mbar_wait(sb + O_BAR + s * 8, 0);
                const uint64_t da = make_desc(st + wg * 8192, 16, 1024), db = make_desc(st + SLOT, 4096, 1024);
                WG_FENCE();
                wgmma_n256(acc, da, db, s);
                wgmma_n256(acc, da + 2, db + 128, 1);
                wgmma_n256(acc, da + 4, db + 1024, 1);
                wgmma_n256(acc, da + 6, db + 1152, 1);
                WG_COMMIT();
                const uint32_t sp = st == sb ? sb + 6 * SLOT : st - 3 * SLOT;
                st += 3 * SLOT; if (st == sb + NS * SLOT) st = sb;
                if (s == 1 && uw == 0 && mt < 14 && elect_one())
                    asm volatile("cp.async.bulk.prefetch.tensor.3d.L2.global [%0, {%1, %2, %3}];" :: "l"(&maps.m[2]), "r"((mt >> 1) * 64), "r"(j * 256 + (mt & 1) * 128), "r"(0) : "memory");
                if (s == 6 && wg == 0) bar_arrive(BAR_PP, 256);
                if (s > 0 && s < 5) {
                    WG_WAIT(1);
                    if (elect_one()) {
                        unsigned old;
                        asm volatile("atom.relaxed.cta.shared.inc.u32 %0, [%1], 7;" : "=r"(old) : "r"(sb + O_REL + s * 4 - 4) : "memory");
                        if (old == 7) {
                            tma_fill(maps.m, sp, sb + O_BAR + (s + 2) * 8, 0, (s + 2) * 64, mt * 128, 0);
                            tma_fill(maps.m, sp + SLOT, sb + O_BAR + (s + 2) * 8, 128, 0, (s + 2) * 64, j * 4);
                            tma_fill(maps.m, sp + 2 * SLOT, sb + O_BAR + (s + 2) * 8, 128, 0, (s + 2) * 64 + 32, j * 4);
                        }
                    }
                    __syncwarp();
                } else if (s == 5 && wg == 0) { WG_WAIT(1); release(4, 21, 3); }
            }
            bar_sync(BAR_A + wg * (BAR_A2 - BAR_A), 256);
            const uint32_t sa = sb + O_STATS + (uw * 16 + g) * 16;
            uint32_t e0 = lds32(sa + q * 4), e1 = lds32(sa + 128 + q * 4);
            if (q == 3) { e0 = 0; e1 = 0; }
            WG_FENCE();
            wgmma_n256_rs(acc, e0, e1, (uint64_t)(((sb + O_BEXT) & 0x3FFFF) >> 4) | ((uint64_t)(128 >> 4) << 32));
            WG_COMMIT();
            if (wg == 1) bar_arrive(BAR_PP, 256);
            const float al0 = ldsf(sa + 12), al1 = ldsf(sa + 140);
            WG_WAIT(1);
            release(6, 24, 6);
            WG_WAIT(0);
            reg_fence(acc);
            const float k00 = 0.7978845608f * al0, k10 = 0.0356774081f * al0 * al0 * al0;
            const float k01 = 0.7978845608f * al1, k11 = 0.0356774081f * al1 * al1 * al1;
            #pragma unroll
            for (int ii = 0; ii < 64; ii++) {
                const int i = ii < 32 ? 63 - ii : ii - 32;
                const float a0 = acc[2 * i], a1 = acc[2 * i + 1], k0 = (i & 1) ? k01 : k00, k1 = (i & 1) ? k11 : k10;
                h[i] = pack_bf16(fmaf(a0, tanh_fast(a0 * fmaf(a0 * a0, k1, k0)), a0), fmaf(a1, tanh_fast(a1 * fmaf(a1 * a1, k1, k0)), a1));
            }
        }
        float accA[32], accB[32];
        uint32_t st = (uint32_t)make_desc(sb + 3 * SLOT, 4096, 1024);
        const uint32_t st_end = (uint32_t)make_desc(sb, 4096, 1024) + NS * (SLOT >> 4);
        auto next_slot = [&]() { const uint32_t d = st; st += SLOT >> 4; if (st == st_end) st -= NS * (SLOT >> 4); return d; };
        auto send = [&](float (&acc)[32], int n) {
            int dest = j + 1 + n; if (dest >= 7) dest -= 7;
            uint4* op = P.S->part + ((mt * 7 + dest) * 7 + j) * 1024 + tid * 4 - lane * 3;
            reg_fence(acc);
            #pragma unroll
            for (int v = 0; v < 4; v++)
                st_relaxed_v4(op + v * 32, make_uint4((pack_bf16(acc[8 * v], acc[8 * v + 1]) & ~1u) | tag, pack_bf16(acc[8 * v + 2], acc[8 * v + 3]),
                                                       pack_bf16(acc[8 * v + 4], acc[8 * v + 5]), pack_bf16(acc[8 * v + 6], acc[8 * v + 7])));
            if (n >= 4 && lane == 0) asm volatile("st.relaxed.gpu.global.u32 [%0], %1;" :: "l"(P.S->pflag + (mt * 7 + dest) * 64 + n * 8 + uw), "r"(epoch) : "memory");
        };
        #pragma unroll 1
        for (int n = 0; n < 6; n += 2) {
            mbar_wait(sb + O_BAR + (7 + n) * 8, 0);
            mbar_wait(sb + O_BAR + (8 + n) * 8, 0);
            const uint32_t d0 = next_slot(), d1 = next_slot(), d2 = next_slot(), d3 = next_slot();
            bar_sync(BAR_PP + wg, 256);
            WG_FENCE();
            wgmma_n64_rs<0>(accA, h[60], h[61], h[62], h[63], d1 + 7 * 128);
            wgmma_n64_rs<0>(accB, h[60], h[61], h[62], h[63], d3 + 7 * 128);
            #pragma unroll
            for (int k = 14; k >= 0; k--) {
                wgmma_n64_rs<1>(accA, h[4 * k], h[4 * k + 1], h[4 * k + 2], h[4 * k + 3], (k < 8 ? d0 : d1) + (k & 7) * 128);
                wgmma_n64_rs<1>(accB, h[4 * k], h[4 * k + 1], h[4 * k + 2], h[4 * k + 3], (k < 8 ? d2 : d3) + (k & 7) * 128);
                if (k == 0) bar_arrive(BAR_PP + (wg ^ 1), 256);
            }
            WG_COMMIT();
            WG_WAIT(0);
            send(accA, n);
            send(accB, n + 1);
            if (release(7 + n, 30 + 2 * n, 4) && n >= 2) {
                if (lane < 2) fetch_part(n - 2 + lane, 6 + (n >> 1));
                if (n == 4) {
                    #pragma unroll 1
                    for (int it = 0; it < (1 << 16); it++) {
                        if (__all_sync(0xffffffffu, ld_relaxed(P.S->pflag + (mt * 7 + j) * 64 + 32 + (lane & 15)) == epoch)) break;
                    }
                    if (lane < 2) fetch_part(4 + lane, 9);
                }
            }
            __syncwarp();
        }
        uint32_t sv[16];
        uint4 xg[4];
        const int oo = (mt * 128 + uw * 16 + (lane >> 3)) * DM + j * 64 + (lane & 7) * 8;
        {
            const uint32_t eye = (g >> 1) == q ? ((g & 1) ? 0x3f800000u : 0x3f80u) : 0u;
            auto take = [&](int r) {
                uint4 p0[4], p1[4];
                #pragma unroll
                for (int v = 0; v < 4; v++) {
                    const uint32_t a = sb + r * SLOT + uw * 2048 + v * 512 + lane * 16;
                    p0[v] = lds128(a); p1[v] = lds128(a + SLOT);
                }
                #pragma unroll 1
                for (int it = 0; it < (1 << 16); it++) {
                    uint32_t m = 0;
                    #pragma unroll
                    for (int v = 0; v < 4; v++) m |= (p0[v].x ^ tag) | (p1[v].x ^ tag);
                    if (!__any_sync(0xffffffffu, m & 1u)) break;
                    int s0 = j - 1 - r, s1 = s0 - 1; if (s0 < 0) s0 += 7; if (s1 < 0) s1 += 7;
                    const uint4* ib = P.S->part + (mt * 7 + j) * 7 * 1024 + tid * 4 - lane * 3;
                    #pragma unroll
                    for (int v = 0; v < 4; v++) { p0[v] = ld_relaxed_v4(ib + s0 * 1024 + v * 32); p1[v] = ld_relaxed_v4(ib + s1 * 1024 + v * 32); }
                }
                #pragma unroll
                for (int v = 0; v < 4; v++) {
                    mma_bf16(accA + 8 * v, p0[v].x, p0[v].y, p1[v].x, p1[v].y, eye);
                    mma_bf16(accA + 8 * v + 4, p0[v].z, p0[v].w, p1[v].z, p1[v].w, eye);
                }
            };
            #pragma unroll
            for (int i = 0; i < 32; i++) accA[i] = 0.f;
            mbar_wait(sb + O_BAR + 13 * 8, 0);
            const uint32_t d0 = next_slot(), d1 = next_slot();
            if (wg == 0) bar_sync(BAR_PP, 256);
            int r = 0;
            #pragma unroll 1
            for (int it = 0; it < (1 << 20); it++) {
                if (r < 6 && __all_sync(0xffffffffu, mbar_test(sb + O_BAR + 56 + r * 4, 1))) { take(r); r += 2; }
                else if (__all_sync(0xffffffffu, mbar_test(sb + O_BAR + 14 * 8, 0))) break;
                else __nanosleep(20);
            }
            WG_FENCE();
            #pragma unroll
            for (int k = 15; k >= 0; k--)
                wgmma_n64_rs<1>(accA, h[4 * k], h[4 * k + 1], h[4 * k + 2], h[4 * k + 3], (k < 8 ? d0 : d1) + (k & 7) * 128);
            WG_COMMIT();
            #pragma unroll
            for (int i = 0; i < 4; i++) xg[i] = __ldg(reinterpret_cast<const uint4*>(P.x + oo + i * 4 * DM));
            WG_WAIT(0);
            reg_fence(accA);
            #pragma unroll 1
            for (; r < 6; r += 2) { mbar_wait(sb + O_BAR + 56 + r * 4, 1); take(r); }
        }
        uint32_t gv[16];
        {
            const float f0 = 0.25f * ldsf(sb + O_STATS + (uw * 16 + g) * 16 + 12), f1 = 0.25f * ldsf(sb + O_STATS + (uw * 16 + g) * 16 + 140);
            #pragma unroll
            for (int i = 0; i < 16; i++) {
                float b0, b1;
                asm volatile("ld.shared.v2.f32 {%0,%1}, [%2];" : "=f"(b0), "=f"(b1) : "r"(sb + O_B2 + (i >> 1) * 32 + q * 8));
                const float h0 = fmaf(accA[2 * i], (i & 1) ? f1 : f0, b0), h1 = fmaf(accA[2 * i + 1], (i & 1) ? f1 : f0, b1);
                gv[i] = pack_bf16(fmaf(h0, tanh_fast(h0), h0), fmaf(h1, tanh_fast(h1), h1));
            }
        }
        bar_sync(BAR_C, 384);
        {
            const uint32_t sa = sb + O_AUX + ((lane >> 4) * 8 + (lane & 7)) * 272 + (uw * 16 + ((lane >> 3) & 1) * 8) * 2;
            #pragma unroll
            for (int i = 0; i < 4; i++) ldsm4t(sa + i * 16 * 272, sv[4 * i], sv[4 * i + 1], sv[4 * i + 2], sv[4 * i + 3]);
        }
        #pragma unroll
        for (int i = 0; i < 16; i++) sv[i] = U32(__hmul2(B2(sv[i]), B2(gv[i])));
        const uint32_t ob = sb + O_SUM + uw * 2304;
        #pragma unroll
        for (int i = 0; i < 4; i++) stsm4(ob + (lane & 15) * 144 + (2 * i + (lane >> 4)) * 16, sv[4 * i], sv[4 * i + 1], sv[4 * i + 2], sv[4 * i + 3]);
        __syncwarp();
        #pragma unroll
        for (int i = 0; i < 4; i++) {
            uint4 v = lds128(ob + (i * 4 + (lane >> 3)) * 144 + (lane & 7) * 16);
            v.x = U32(__hadd2(B2(xg[i].x), B2(v.x))); v.y = U32(__hadd2(B2(xg[i].y), B2(v.y)));
            v.z = U32(__hadd2(B2(xg[i].z), B2(v.z))); v.w = U32(__hadd2(B2(xg[i].w), B2(v.w)));
            *reinterpret_cast<uint4*>(P.out + oo + i * 4 * DM) = v;
        }
    } else {
        const int at = tid - 256;
        if (tt < 32) wait_hint(P.S->hint + (8 + ch / 112) * 32, epoch * 128);
        bar_sync(1 + team, 64);
        fetch_x(P, ch, tb, tt);
        Taps T = sum_deposits<2>(tb + T_STG, STG_W, 0, tt);
        #pragma unroll 1
        for (;;) {
            int tq = tt; uint32_t tbq = tb; asm volatile("" : "+r"(tq), "+r"(tbq));
            scatter_taps(T, tbq, tq);
            if (tq == 0) sts128(tbq + T_TAB + TABSZ, __float_as_uint(T.yscale), epoch, (is_mlp || ch >= CH_EXP) ? DM : CH_EXP + team * NHELP + NCTA - 1 - b, 0);
            prep(P, ch, tbq, tq, 1 + team, tag);
            const int cb = (team & 1) ? 13 : 7, gi = team >> 1, nxt = ch < CH_EXP ? 0 : (gi == 2 ? DM : ch + 2 * NHELP);
            convolve(P, ch, tbq, tq, 1 + team,
                     (is_mlp || (gi == 0 && ch < CH_EXP)) ? -1 : cb + gi, (is_mlp || nxt >= DM) ? -1 : cb + (gi == 2 ? 0 : gi + 1));
            epoch = lds32(tbq + T_TAB + TABSZ + 4); tag = epoch & 1;
            ch = lds32(tbq + T_TAB + TABSZ + 8);
            if (ch >= DM) break;
            uint4 e0, e1;
            #pragma unroll 1
            for (int it = 0; it < (1 << 16); it++) {
                e0 = ld_relaxed_v4(P.S->kexp + (ch - CH_EXP) * 128 + tq); e1 = ld_relaxed_v4(P.S->kexp + (ch - CH_EXP) * 128 + 64 + tq);
                if (it == 0) { bar_sync(1 + team, 64); fetch_x(P, ch, tbq, tq); }
                if (!__any_sync(0xffffffffu, ((e0.w ^ tag) | (e1.w ^ tag)) & 1u)) break;
            }
            T.kv[0] = e0.x; T.kv[1] = e0.y; T.kv[2] = e0.z; T.kv[3] = e1.x; T.kv[4] = e1.y;
            T.k2 = __uint_as_float(e0.w); T.yscale = __uint_as_float(e1.z);
        }
        if (!is_mlp) { if (tid == 0) P.S->cnt[b * 8] = epoch; return; }
        bar_sync(BAR_AUX, 128);
        {
            wait_hint(P.S->hint + (1 + j) * 32, epoch * 128 - 16);
            uint4 sv[8];
            #pragma unroll
            for (int v = 0; v < 8; v++) sv[v].x = tag ^ 1u;
            #pragma unroll 1
            for (int it = 0; it < (1 << 16); it++) {
                uint32_t m = 0;
                #pragma unroll
                for (int v = 0; v < 8; v++)
                    if ((sv[v].x ^ tag) & 1u) sv[v] = ld_relaxed_v4(P.S->sT + (j * 64 + v * 8 + (at >> 4)) * LSEQ + mt * 128 + (at & 15) * 8);
                #pragma unroll
                for (int v = 0; v < 8; v++) m |= sv[v].x ^ tag;
                if (!__any_sync(0xffffffffu, m & 1u)) break;
            }
            #pragma unroll
            for (int v = 0; v < 8; v++) sts128(sb + O_AUX + (v * 8 + (at >> 4)) * 272 + (at & 15) * 16, sv[v].x, sv[v].y, sv[v].z, sv[v].w);
        }
        bar_arrive(BAR_C, 384);
    }
}

__device__ __forceinline__ float bfv(const __nv_bfloat16* p, int i) { return __bfloat162float(p[i]); }
__global__ void fb_ln(const __nv_bfloat16* x, __nv_bfloat16* y) {
    const int row = blockIdx.x, lane = threadIdx.x;
    float s = 0.f, v = 0.f;
    for (int i = lane; i < DM; i += 32) s += bfv(x, row * DM + i);
    for (int o = 16; o > 0; o >>= 1) s += __shfl_xor_sync(0xffffffffu, s, o);
    s *= 1.f / DM;
    for (int i = lane; i < DM; i += 32) { const float d = bfv(x, row * DM + i) - s; v += d * d; }
    for (int o = 16; o > 0; o >>= 1) v += __shfl_xor_sync(0xffffffffu, v, o);
    const float den = rbf(sqrtf(rbf(rbf(v * (1.f / DM)) + 1e-5f)));
    for (int i = lane; i < DM; i += 32) y[row * DM + i] = __float2bfloat16(rbf(bfv(x, row * DM + i) - rbf(s)) / den);
}
__global__ void fb_kernel(const Params P, float* K) {
    const int d = blockIdx.y, l = blockIdx.x * 256 + threadIdx.x;
    const float dt = rbf(expf(bfv(P.ldt, d))), pos = rbf((float)l);
    float a = 0.f;
    for (int n = 0; n < NMODE; n++) {
        float sn, cs;
        sincosf(bfv(P.aim, d * NMODE + n) * dt * pos, &sn, &cs);
        a += expf(-rbf(expf(bfv(P.lar, d * NMODE + n))) * dt * pos) * dt * (bfv(P.cre, d * NMODE + n) * cs - bfv(P.cim, d * NMODE + n) * sn);
    }
    K[l * DM + d] = 2.f * a;
}
__global__ void fb_hidden(const Params P, const __nv_bfloat16* y2, __nv_bfloat16* h) {
    const int t = blockIdx.y, f = blockIdx.x * 256 + threadIdx.x;
    float a = 0.f;
    for (int k = 0; k < DM; k++) a += bfv(y2, t * DM + k) * bfv(P.w1, k * FF + f);
    a = rbf(rbf(a) + bfv(P.b1, f));
    h[t * FF + f] = __float2bfloat16(0.5f * a * (1.f + tanhf(0.7978845608f * a + 0.0356774081f * a * a * a)));
}
__global__ void fb_out(const Params P, const __nv_bfloat16* w2, const __nv_bfloat16* xn, const float* K, const __nv_bfloat16* h) {
    const int t = blockIdx.x, d = threadIdx.x;
    float y = 0.f, o = 0.f;
    for (int l = 0; l <= t; l++) y += K[l * DM + d] * bfv(xn, (t - l) * DM + d);
    for (int f = 0; f < FF; f++) o += bfv(h, t * FF + f) * bfv(w2, f * DM + d);
    o = rbf(rbf(o) + bfv(P.b2, d));
    const float sv = rbf(rbf(y) + rbf(bfv(xn, t * DM + d) * bfv(P.dsk, d)));
    P.out[t * DM + d] = __float2bfloat16(bfv(P.x, t * DM + d) + rbf(sv * rbf(o / (1.f + expf(-o)))));
}

typedef CUresult (*EncodeFn)(CUtensorMap*, CUtensorMapDataType, cuuint32_t, void*, const cuuint64_t*, const cuuint64_t*, const cuuint32_t*,
                             const cuuint32_t*, CUtensorMapInterleave, CUtensorMapSwizzle, CUtensorMapL2promotion, CUtensorMapFloatOOBfill);

}

extern "C" void kernel_launch(void* const* d_in, const int* in_sizes, int n_in, void* d_out, int out_size) {
    (void)in_sizes; (void)n_in; (void)out_size;
    static EncodeFn enc = nullptr;
    static Scratch* scr = nullptr;
    static int resident = 0;
    if (!scr) {
        void* fn = nullptr; cudaDriverEntryPointQueryResult qr;
        cudaGetDriverEntryPoint("cuTensorMapEncodeTiled", &fn, cudaEnableDefault, &qr);
        enc = (EncodeFn)fn;
        cudaGetSymbolAddress((void**)&scr, g_scr);
        cudaFuncSetAttribute(fused_kernel, cudaFuncAttributeMaxDynamicSharedMemorySize, SMEM_BYTES);
        int dev = 0, sms = 0, per_sm = 0;
        cudaGetDevice(&dev);
        cudaDeviceGetAttribute(&sms, cudaDevAttrMultiProcessorCount, dev);
        cudaOccupancyMaxActiveBlocksPerMultiprocessor(&per_sm, fused_kernel, 384, SMEM_BYTES);
        resident = sms * per_sm;
    }
    Params P;
    P.x = (const __nv_bfloat16*)d_in[0]; P.lar = (const __nv_bfloat16*)d_in[1]; P.aim = (const __nv_bfloat16*)d_in[2];
    P.cre = (const __nv_bfloat16*)d_in[3]; P.cim = (const __nv_bfloat16*)d_in[4]; P.ldt = (const __nv_bfloat16*)d_in[5];
    P.dsk = (const __nv_bfloat16*)d_in[6]; P.w1 = (const __nv_bfloat16*)d_in[8]; P.b1 = (const __nv_bfloat16*)d_in[9];
    P.b2 = (const __nv_bfloat16*)d_in[11]; P.out = (__nv_bfloat16*)d_out; P.S = scr;
    if (FORCE_FALLBACK || resident < NCTA || !enc) {
        cudaStream_t st = cudaStreamPerThread;
        __nv_bfloat16 *xn = (__nv_bfloat16*)scr->xnT, *y2 = scr->sT, *h = (__nv_bfloat16*)scr->part;
        float* K = (float*)(h + LSEQ * FF);
        fb_ln<<<LSEQ, 32, 0, st>>>(P.x, xn);
        fb_ln<<<LSEQ, 32, 0, st>>>(xn, y2);
        fb_kernel<<<dim3(LSEQ / 256, DM), 256, 0, st>>>(P, K);
        fb_hidden<<<dim3(FF / 256, LSEQ), 256, 0, st>>>(P, y2, h);
        fb_out<<<LSEQ, DM, 0, st>>>(P, (const __nv_bfloat16*)d_in[10], xn, K, h);
        return;
    }
    Maps maps;
    const cuuint32_t es[3] = {1, 1, 1};
    { cuuint64_t gd[3] = {DM, LSEQ, 1}; cuuint64_t gs[2] = {DM * 2, (cuuint64_t)DM * 2 * LSEQ}; cuuint32_t bd[3] = {64, 128, 1};
      enc(&maps.m[0], CU_TENSOR_MAP_DATA_TYPE_BFLOAT16, 3, d_in[0], gd, gs, bd, es, CU_TENSOR_MAP_INTERLEAVE_NONE, CU_TENSOR_MAP_SWIZZLE_128B, CU_TENSOR_MAP_L2_PROMOTION_L2_128B, CU_TENSOR_MAP_FLOAT_OOB_FILL_NONE); }
    { cuuint64_t gd[3] = {64, DM, FF / 64}; cuuint64_t gs[2] = {FF * 2, 128}; cuuint32_t bd[3] = {64, 32, 4};
      enc(&maps.m[1], CU_TENSOR_MAP_DATA_TYPE_BFLOAT16, 3, d_in[8], gd, gs, bd, es, CU_TENSOR_MAP_INTERLEAVE_NONE, CU_TENSOR_MAP_SWIZZLE_128B, CU_TENSOR_MAP_L2_PROMOTION_L2_128B, CU_TENSOR_MAP_FLOAT_OOB_FILL_NONE); }
    { cuuint64_t gd[3] = {DM, FF, 1}; cuuint64_t gs[2] = {DM * 2, (cuuint64_t)DM * 2 * FF}; cuuint32_t bd[3] = {64, 128, 1};
      enc(&maps.m[2], CU_TENSOR_MAP_DATA_TYPE_BFLOAT16, 3, d_in[10], gd, gs, bd, es, CU_TENSOR_MAP_INTERLEAVE_NONE, CU_TENSOR_MAP_SWIZZLE_128B, CU_TENSOR_MAP_L2_PROMOTION_L2_128B, CU_TENSOR_MAP_FLOAT_OOB_FILL_NONE); }
    fused_kernel<<<NCTA, 384, SMEM_BYTES, cudaStreamPerThread>>>(P, maps);
}
```
